```python
import torch

def _softmax(x, axis=-1):
    return torch.softmax(x, dim=axis)
def _gelu(x):
    return torch.nn.functional.gelu(x, approximate="tanh")
def _silu(x):
    return torch.nn.functional.silu(x)
def _sigmoid(x):
    return torch.sigmoid(x)
def _layernorm(x, axis=-1, eps=1e-5):
    m = x.mean(dim=axis, keepdim=True)
    v = x.var(dim=axis, keepdim=True, unbiased=False)
    return (x - m) / torch.sqrt(v + eps)
def _scatter_add(tgt, idx, src, axis=0):
    return tgt.clone().index_add_(axis, idx, src)
def _segment_sum(src, seg, n):
    out = torch.zeros((n,) + src.shape[1:], dtype=src.dtype)
    return out.index_add_(0, seg, src)
def _pad(x, pw):
    flat = tuple(v for pair in reversed(pw) for v in pair)
    return torch.nn.functional.pad(x, flat)

kernel_name = 'sequential_preLN__mha_block_cached__glu_gated_geglu__decode'

def setup_inputs():

    _w = (lambda a: (lambda t: t.to(torch.bfloat16) if t.is_floating_point() else t)(torch.as_tensor(a)))
    def _A_setup():
        B, Sq, D = 1, 1, 576
        H, Sk, Dh = 32, 16384, 128
        return {
            "x": _w((lambda *s: torch.randn(*s, dtype=torch.bfloat16) * 0.05)(B, Sq, D)),
            "k_cache": _w((lambda *s: torch.randn(*s, dtype=torch.bfloat16) * 3.2)(B, H, Sk, Dh)),
            "v_cache": _w((lambda *s: torch.randn(*s, dtype=torch.bfloat16) * 1.6)(B, H, Sk, Dh)),
            "wq": _w((lambda *s: torch.randn(*s, dtype=torch.bfloat16) * 3.2)(D, H * Dh) * (D ** -0.5)),
            "wo": _w((lambda *s: torch.randn(*s, dtype=torch.bfloat16) * 1.6)(H * Dh, D) * ((H * Dh) ** -0.5)),
        }
    _A_in = _A_setup()

    def _B_setup():
        B, S, Dm, Df = 1, 1, 576, 4608
        return {
            "x": _w((lambda *s: torch.randn(*s, dtype=torch.bfloat16) * 0.05)(B, S, Dm)),
            "w_gate": _w((lambda *s: torch.randn(*s, dtype=torch.bfloat16) * 1.6)(Dm, Df) * (Dm ** -0.5)),
            "w_up": _w((lambda *s: torch.randn(*s, dtype=torch.bfloat16) * 1.6)(Dm, Df) * (Dm ** -0.5)),
            "w_down": _w((lambda *s: torch.randn(*s, dtype=torch.bfloat16) * 1.6)(Df, Dm) * (Df ** -0.5)),
        }
    _B_in = _B_setup()

    return {
        "A_x": _A_in["x"],
        "A_k_cache": _A_in["k_cache"],
        "A_v_cache": _A_in["v_cache"],
        "A_wq": _A_in["wq"],
        "A_wo": _A_in["wo"],
        "B_x": _B_in["x"],
        "B_w_gate": _B_in["w_gate"],
        "B_w_up": _B_in["w_up"],
        "B_w_down": _B_in["w_down"],
    }

def reference(A_x, A_k_cache, A_v_cache, A_wq, A_wo, B_x, B_w_gate, B_w_up, B_w_down):
    def _A_ref(x, k_cache, v_cache, wq, wo):
        B, Sq, D = x.shape
        H, Dh = 32, 128
        q = (lambda x, *d: x.permute(*d))((x @ wq).reshape(B, Sq, H, Dh), 0, 2, 1, 3)
        scores = torch.einsum("bhqd,bhkd->bhqk", q, k_cache) * (Dh ** -0.5)
        p = _softmax(scores, axis=-1)
        o = torch.einsum("bhqk,bhkd->bhqd", p, v_cache)
        return (lambda x, *d: x.permute(*d))(o, 0, 2, 1, 3).reshape(B, Sq, H * Dh) @ wo

    def _B_ref(x, w_gate, w_up, w_down):
        g = torch.einsum("bsd,df->bsf", x, w_gate)
        u = torch.einsum("bsd,df->bsf", x, w_up)
        h = _gelu(g) * u
        return torch.einsum("bsf,fd->bsd", h, w_down)

    x = A_x
    h = x + _A_ref(_layernorm(x, axis=-1), A_k_cache, A_v_cache, A_wq, A_wo)
    h2 = h + _B_ref(_layernorm(h, axis=-1), B_w_gate, B_w_up, B_w_down)
    return h2
```

```cpp
#include <cuda_runtime.h>
#include <cuda_bf16.h>
#include <cuda.h>
#include <stdint.h>

#define DEVINL __device__ __forceinline__
typedef unsigned long long ull;
typedef __nv_bfloat16 bf16;

namespace {

constexpr int D_MODEL = 576;
constexpr int NCTA = 132;
constexpr int NOWN = 128;
constexpr int NGRP = 4;
constexpr int GSZ = 33;
constexpr int HPG = 8;
constexpr int TBYTES = 16384;
constexpr int UPG = 2048;
constexpr int NSLOT = 9;
#define INFL_TILES 4
#define GU_GATE 0
#define DN_LATE 6
#define PARK_N 0
#define PARK_L PARK_N
#define PARK_AT 66
#define CLR_HEAD 5
#define INFL_TAIL 2
constexpr int INFL = INFL_TILES;
constexpr int NREP = 4;
#define LOOK 1
constexpr int NTHREADS = 288;
constexpr int NEARLY = 112;
constexpr int LATE0 = 80;
constexpr int NLATE = 48;
constexpr int NRED = 72;
constexpr int RECW = 132;
constexpr uint32_t END_MARK = 0xFFFFFFFFu;
constexpr uint32_t WO_MARK = 0xFFFFFFFEu;
constexpr uint32_t GU_MARK = 0xFFFFFFFDu;
constexpr long long WAIT_LIMIT = 200000000LL;

constexpr int RPITCH = 1168;
constexpr int OFF_DN = NSLOT * TBYTES;
constexpr int OFF_WL = OFF_DN + 42112;
constexpr int OFF_Q = OFF_WL + 12288;
constexpr int OFF_RED = OFF_Q + 4096;
constexpr int OFF_RED2 = OFF_RED + 8448;
constexpr int OFF_XS = OFF_RED2 + 4096;
constexpr int OFF_HS = OFF_XS + 2304;
constexpr int OFF_VN = OFF_HS + 2304;
constexpr int OFF_ST = OFF_VN + 1152;
constexpr int OFF_OS = OFF_ST + 272;
constexpr int OFF_HH = OFF_OS + 256;
constexpr int OFF_DESC = OFF_HH + 96;
constexpr int OFF_CLM = OFF_DESC + 64;
constexpr int OFF_LNP = OFF_CLM + 32;
constexpr int OFF_TC = OFF_LNP + 128;
constexpr int OFF_BAR = OFF_TC + 256;
constexpr int BAR_DN = OFF_BAR + 2 * NSLOT * 8;
constexpr int BAR_WQ = BAR_DN + 8;
constexpr int BAR_GU = BAR_WQ + 3 * 8;
constexpr int BAR_WL = BAR_GU + 8;
constexpr int SMEM_BYTES = BAR_WL + 8;
static_assert(SMEM_BYTES <= 232448, "smem");
static_assert(OFF_LNP % 16 == 0 && OFF_BAR % 8 == 0 && OFF_OS % 16 == 0 && OFF_HH % 16 == 0, "align");

__device__ unsigned int g_epoch;
__device__ __align__(16) unsigned int g_ctr[NGRP];
__device__ __align__(128) ull g_q[4096];
__device__ __align__(128) ull g_opart[32 * GSZ * RECW];
__device__ __align__(128) ull g_attn1[NEARLY * D_MODEL];
__device__ __align__(128) ull g_attn2[NREP * NGRP * D_MODEL];
__device__ __align__(128) ull g_pre[NLATE * 2];
__device__ __align__(128) ull g_down[NRED * NOWN * 8];

#define TL(i)
#define TC(i)

DEVINL uint32_t smem_u32(const void* p) { return (uint32_t)__cvta_generic_to_shared(p); }
DEVINL void mbar_init(uint32_t bar, uint32_t cnt) {
    asm volatile("mbarrier.init.shared::cta.b64 [%0], %1;" ::"r"(bar), "r"(cnt) : "memory");
}
DEVINL void mbar_expect_tx(uint32_t bar, uint32_t bytes) {
    asm volatile("mbarrier.arrive.expect_tx.shared::cta.b64 _, [%0], %1;" ::"r"(bar), "r"(bytes) : "memory");
}
DEVINL void mbar_arrive(uint32_t bar) {
    asm volatile("mbarrier.arrive.shared::cta.b64 _, [%0];" ::"r"(bar) : "memory");
}
__device__ __noinline__ long long wait_check(long long t0) {
    const long long t = clock64();
    if (t0 == 0) return t;
    if (t - t0 > WAIT_LIMIT) __trap();
    return t0;
}
DEVINL void mbar_wait(uint32_t bar, uint32_t parity) {
    uint32_t ok;
    uint32_t it = 0;
    long long t0 = 0;
    while (true) {
        asm volatile(
            "{\n.reg .pred p;\nmbarrier.try_wait.parity.shared::cta.b64 p, [%1], %2;\nselp.u32 %0, 1, 0, p;\n}"
            : "=r"(ok)
            : "r"(bar), "r"(parity)
            : "memory");
        if (ok) break;
        if ((++it & 63u) == 0) t0 = wait_check(t0);
    }
}
DEVINL void bulk_load(uint32_t dst, const void* src, uint32_t bytes, uint32_t bar, uint64_t pol) {
    asm volatile(
        "cp.async.bulk.shared::cluster.global.mbarrier::complete_tx::bytes.L2::cache_hint [%0], [%1], %2, [%3], %4;" ::"r"(dst),
        "l"(src), "r"(bytes), "r"(bar), "l"(pol)
        : "memory");
}
DEVINL void tma2d(uint32_t dst, const CUtensorMap* map, int c0, int c1, uint32_t bar, uint64_t pol) {
    asm volatile(
        "cp.async.bulk.tensor.2d.shared::cluster.global.mbarrier::complete_tx::bytes.L2::cache_hint [%0], [%1, {%3, %4}], [%2], %5;" ::"r"(dst),
        "l"((uint64_t)map), "r"(bar), "r"(c0), "r"(c1), "l"(pol)
        : "memory");
}
DEVINL void cons_sync() { asm volatile("bar.sync 1, 256;" ::: "memory"); }

DEVINL void ldsm_x4t(uint32_t addr, uint32_t (&r)[4]) {
    asm volatile("ldmatrix.sync.aligned.m8n8.x4.trans.shared.b16 {%0,%1,%2,%3}, [%4];"
                 : "=r"(r[0]), "=r"(r[1]), "=r"(r[2]), "=r"(r[3])
                 : "r"(addr)
                 : "memory");
}
DEVINL void ldsm_x2t(uint32_t addr, uint32_t& r0, uint32_t& r1) {
    asm volatile("ldmatrix.sync.aligned.m8n8.x2.trans.shared.b16 {%0,%1}, [%2];" : "=r"(r0), "=r"(r1) : "r"(addr) : "memory");
}
DEVINL void ldsm_x1t(uint32_t addr, uint32_t& r0) {
    asm volatile("ldmatrix.sync.aligned.m8n8.x1.trans.shared.b16 {%0}, [%1];" : "=r"(r0) : "r"(addr) : "memory");
}
DEVINL uint32_t lds32(uint32_t addr) {
    uint32_t r;
    asm volatile("ld.shared.u32 %0, [%1];" : "=r"(r) : "r"(addr) : "memory");
    return r;
}
DEVINL void mma_vec(float (&c)[4], uint32_t a_lo, uint32_t a_hi, uint32_t b0, uint32_t b1) {
    asm("mma.sync.aligned.m16n8k16.row.col.f32.bf16.bf16.f32 {%0,%1,%2,%3}, {%4,%5,%6,%7}, {%8,%9}, {%0,%1,%2,%3};"
        : "+f"(c[0]), "+f"(c[1]), "+f"(c[2]), "+f"(c[3])
        : "r"(a_lo), "r"(0u), "r"(a_hi), "r"(0u), "r"(b0), "r"(b1));
}

DEVINL uint32_t pack_bf16(float lo, float hi) {
    uint32_t r;
    asm("cvt.rn.bf16x2.f32 %0, %1, %2;" : "=r"(r) : "f"(hi), "f"(lo));
    return r;
}
DEVINL float bf16r(float v) { return __uint_as_float(pack_bf16(0.f, v) & 0xffff0000u); }
DEVINL float bf_lo(uint32_t w) { return __uint_as_float(w << 16); }
DEVINL float bf_hi(uint32_t w) { return __uint_as_float(w & 0xffff0000u); }

DEVINL ull ll_pack(float v, uint32_t tag) { return ((ull)tag << 32) | (ull)__float_as_uint(v); }
DEVINL void ll_store1(ull* p, float a, uint32_t tag) {
    asm volatile("st.relaxed.gpu.global.u64 [%0], %1;" ::"l"(p), "l"(ll_pack(a, tag)) : "memory");
}
DEVINL void ll_store2(ull* p, float a, float b, uint32_t tag) {
    asm volatile("st.relaxed.gpu.global.v2.u64 [%0], {%1, %2};" ::"l"(p), "l"(ll_pack(a, tag)), "l"(ll_pack(b, tag)) : "memory");
}
DEVINL void ll_load2(const ull* p, ull& a, ull& b) {
    asm volatile("ld.relaxed.gpu.global.v2.u64 {%0, %1}, [%2];" : "=l"(a), "=l"(b) : "l"(p) : "memory");
}
DEVINL bool ll_ok(ull a, ull b, uint32_t tag) { return (uint32_t)(a >> 32) == tag && (uint32_t)(b >> 32) == tag; }
DEVINL float ll_val(ull a) { return __uint_as_float((uint32_t)a); }

template <int N, class F>
DEVINL void ll_pollf(F addr, uint32_t pend, float (&v)[N][2], uint32_t tag) {
#pragma unroll
    for (int i = 0; i < N; i++) v[i][0] = v[i][1] = 0.f;
    uint32_t it = 0;
    long long t0 = 0;
    while (pend) {
        ull a[N], b[N];
#pragma unroll
        for (int i = 0; i < N; i++)
            if (pend >> i & 1u) ll_load2(addr(i), a[i], b[i]);
#pragma unroll
        for (int i = 0; i < N; i++)
            if ((pend >> i & 1u) && ll_ok(a[i], b[i], tag)) {
                v[i][0] = ll_val(a[i]);
                v[i][1] = ll_val(b[i]);
                pend &= ~(1u << i);
            }
        if ((++it & 63u) == 0) t0 = wait_check(t0);
    }
}
template <int N>
DEVINL void ll_poll(const ull* base, int stride, int cnt, float (&v)[N][2], uint32_t tag) {
    ll_pollf<N>([&](int i) { return base + i * stride; }, (1u << cnt) - 1u, v, tag);
}

DEVINL float warp_sum(float v) {
#pragma unroll
    for (int o = 16; o > 0; o >>= 1) v += __shfl_xor_sync(0xffffffffu, v, o);
    return v;
}
DEVINL float warp_max(float v) {
#pragma unroll
    for (int o = 16; o > 0; o >>= 1) v = fmaxf(v, __shfl_xor_sync(0xffffffffu, v, o));
    return v;
}

DEVINL void ln_block(unsigned char* smem, const float (&v)[4], int tid) {
    float* part = (float*)(smem + OFF_LNP);
    float mu = 0.5f * (v[0] + v[1]), m2 = 0.5f * (v[0] - v[1]) * (v[0] - v[1]), hn = 1.0f;
    if (tid < 32) {
        const float mu2 = 0.5f * (v[2] + v[3]), d = mu - mu2;
        m2 += fmaf(d, d, 0.5f * (v[2] - v[3]) * (v[2] - v[3]));
        mu = 0.5f * (mu + mu2);
        hn = 2.0f;
    }
#pragma unroll
    for (int o = 16; o > 0; o >>= 1) {
        const float mo = __shfl_xor_sync(0xffffffffu, mu, o), so = __shfl_xor_sync(0xffffffffu, m2, o);
        const float d = mu - mo;
        m2 = fmaf(d * d, hn, m2 + so);
        mu = 0.5f * (mu + mo);
        hn *= 2.0f;
    }
    if ((tid & 31) == 0) *(float2*)(part + 2 * (tid >> 5)) = make_float2(mu, m2);
    TC(10);
    cons_sync();
    TC(11);
    const float4 q0 = *(const float4*)part, q1 = *(const float4*)(part + 4), q2 = *(const float4*)(part + 8),
                 q3 = *(const float4*)(part + 12);
    const float mean = (((q0.x + q0.x) + q0.z) + (q1.x + q1.z) + ((q2.x + q2.z) + (q3.x + q3.z))) * (1.0f / 9.0f);
    const float d0 = q0.x - mean, d1 = q0.z - mean, d2 = q1.x - mean, d3 = q1.z - mean, d4 = q2.x - mean,
                d5 = q2.z - mean, d6 = q3.x - mean, d7 = q3.z - mean;
    const float dd = ((2.0f * d0 * d0 + d1 * d1) + (d2 * d2 + d3 * d3)) + ((d4 * d4 + d5 * d5) + (d6 * d6 + d7 * d7));
    const float M2 = fmaf(64.0f, dd, ((q0.y + q0.w) + (q1.y + q1.w)) + ((q2.y + q2.w) + (q3.y + q3.w)));
    const float mb = bf16r(mean);
    const float vb = bf16r(M2 * (1.0f / 576.0f));
    const float den = bf16r(sqrtf(bf16r(vb + 1e-5f)));
    uint32_t* vn2 = (uint32_t*)(smem + OFF_VN);
    const uint32_t n0 = pack_bf16(bf16r(v[0] - mb) / den, bf16r(v[1] - mb) / den);
    vn2[tid] = n0;
    if (tid < 32) {
        const uint32_t n1 = pack_bf16(bf16r(v[2] - mb) / den, bf16r(v[3] - mb) / den);
        vn2[256 + tid] = n1;
    }
    TC(12);
}

__device__ __noinline__ void q_phase(unsigned char* smem, const bf16* __restrict__ x, bool owner, uint32_t tag) {
    const int tid = threadIdx.x, w = tid >> 5, lane = tid & 31;
    const int cta = blockIdx.x, grp = cta % NGRP;
    const uint32_t sbase = smem_u32(smem);
    float* xs = (float*)(smem + OFF_XS);
    float* red2 = (float*)(smem + OFF_RED2);
    float* qs = (float*)(smem + OFF_Q);
    if (owner) {
        const uint32_t* x2 = (const uint32_t*)x;
        const uint32_t xa = __ldg(x2 + tid), xb = tid < 32 ? __ldg(x2 + 256 + tid) : 0u;
        const float xv4[4] = {bf_lo(xa), bf_hi(xa), bf_lo(xb), bf_hi(xb)};
        *(float2*)(xs + 2 * tid) = make_float2(xv4[0], xv4[1]);
        if (tid < 32) *(float2*)(xs + 512 + 2 * tid) = make_float2(xv4[2], xv4[3]);
        ln_block(smem, xv4, tid);
    }
    asm volatile("bar.sync 2, 288;" ::: "memory");
    if (owner) {
        float c0[4] = {0.f, 0.f, 0.f, 0.f}, c1[4] = {0.f, 0.f, 0.f, 0.f};
        const int nh = w >> 2, kq = w & 3;
        const uint32_t lrow = ((lane >> 3) & 1) * 8 + (lane & 7);
        const uint32_t lcol = (2 * nh + (lane >> 4)) * 16;
        const uint32_t vn_a = sbase + OFF_VN + (lane & 3) * 4;
#pragma unroll
        for (int p = 0; p < 3; p++) {
            mbar_wait(sbase + BAR_WQ + 8 * p, 0);
#pragma unroll
            for (int s = 0; s < 3; s++) {
                uint32_t b[4];
                ldsm_x4t(sbase + OFF_DN + p * 15360 + ((3 * kq + s) * 16 + lrow) * 80 + lcol, b);
                const uint32_t ka = vn_a + (192 * p + (3 * kq + s) * 16) * 2;
                const uint32_t al = lds32(ka), ah = lds32(ka + 16);
                mma_vec(c0, al, ah, b[0], b[1]);
                mma_vec(c1, al, ah, b[2], b[3]);
            }
        }
        if (lane < 4) {
            float* r = red2 + kq * 32 + nh * 16 + 2 * lane;
            r[0] = c0[0];
            r[1] = c0[1];
            r[8] = c1[0];
            r[9] = c1[1];
        }
        cons_sync();
        if (tid < 32) {
            const float q = bf16r((red2[tid] + red2[32 + tid]) + (red2[64 + tid] + red2[96 + tid]));
            ll_store1(&g_q[32 * cta + tid], q, tag);
        }
    }
    TL(1);
    float v[2][2];
    ll_poll<2>(g_q + grp * 1024 + 2 * tid, 512, 2, v, tag);
    *(float2*)(qs + 2 * tid) = make_float2(v[0][0], v[0][1]);
    *(float2*)(qs + 2 * tid + 512) = make_float2(v[1][0], v[1][1]);
    cons_sync();
}

DEVINL float record_weights(const float* st, int lane, float& wb) {
    const float2 sa = *(const float2*)(st + 2 * lane), sb = *(const float2*)(st + 64);
    const float M = fmaxf(warp_max(sa.x), sb.x);
    const float ea = sa.x == -INFINITY ? 0.f : __expf(sa.x - M);
    const float eb = sb.x == -INFINITY ? 0.f : __expf(sb.x - M);
    const float inv = 1.0f / fmaf(eb, sb.y, warp_sum(ea * sa.y));
    wb = eb * inv;
    return ea * inv;
}

__device__ __noinline__ void early_duty(unsigned char* smem, int slot, uint32_t ph, uint32_t parked, uint32_t tag) {
    const int tid = threadIdx.x, w = tid >> 5, lane = tid & 31;
    const int e = blockIdx.x, oh = (e / 28) * HPG + (e >> 2) % 7, oj = e & 3;
    const uint32_t sbase = smem_u32(smem);
    float* red2 = (float*)(smem + OFF_RED2);
    float* st = (float*)(smem + OFF_ST);
    const ull* rec = g_opart + (size_t)oh * GSZ * RECW;
    {
        float ov[3][2];
        const bool has_st = tid >= 64 && tid < 64 + GSZ;
        const ull* base = rec + (tid >> 4) * RECW + 32 * oj + 2 * (tid & 15);
        const ull* last = tid < 16 ? base + 32 * RECW : rec + (tid - 64) * RECW + 128;
        ll_pollf<3>([&](int i) { return i == 2 ? last : base + i * 16 * RECW; }, (tid < 16 || has_st) ? 7u : 3u, ov, tag);
        if (has_st) *(float2*)(st + 2 * (tid - 64)) = make_float2(ov[2][0], ov[2][1]);
        cons_sync();
        float wb;
        const float wa = record_weights(st, lane, wb);
        const float w0 = __shfl_sync(0xffffffffu, wa, tid >> 4), w1 = __shfl_sync(0xffffffffu, wa, (tid >> 4) + 16);
        float s0 = fmaf(w0, ov[0][0], w1 * ov[1][0]), s1 = fmaf(w0, ov[0][1], w1 * ov[1][1]);
        if (tid < 16) {
            s0 = fmaf(wb, ov[2][0], s0);
            s1 = fmaf(wb, ov[2][1], s1);
        }
        s0 += __shfl_xor_sync(0xffffffffu, s0, 16);
        s1 += __shfl_xor_sync(0xffffffffu, s1, 16);
        if (lane < 16) *(float2*)(red2 + w * 32 + 2 * lane) = make_float2(s0, s1);
    }
    cons_sync();
    uint32_t pk;
    {
        float s0 = 0.f, s1 = 0.f;
#pragma unroll
        for (int i = 0; i < 8; i++) {
            const float2 t = *(const float2*)(red2 + i * 32 + 2 * (lane & 15));
            s0 += t.x;
            s1 += t.y;
        }
        pk = pack_bf16(s0, s1);
    }
    const uint32_t a0 = __shfl_sync(0xffffffffu, pk, lane & 3), a1 = __shfl_sync(0xffffffffu, pk, 4 + (lane & 3));
    const uint32_t a2 = __shfl_sync(0xffffffffu, pk, 8 + (lane & 3)), a3 = __shfl_sync(0xffffffffu, pk, 12 + (lane & 3));
    uint32_t row;
    {
        int s = slot;
        uint32_t p2 = ph;
        row = 0;
#pragma unroll
        for (int t = 0; t < 3; t++) {
            mbar_wait(sbase + OFF_BAR + 8 * s, p2);
            if (lane / 11 == t) row = sbase + s * TBYTES + (lane % 11) * RPITCH + w * 144;
            do {
                if (++s == NSLOT) {
                    s = 0;
                    p2 ^= 1;
                }
            } while (parked >> s & 1u);
        }
    }
    float r0 = 0.f, r1 = 0.f, r2 = 0.f, r3 = 0.f;
#pragma unroll
    for (int j = 0; j < 9; j++) {
        uint32_t b[4];
        ldsm_x4t(row + j * 16, b);
        float c[4] = {0.f, 0.f, 0.f, 0.f};
        mma_vec(c, a0, a1, b[0], b[1]);
        mma_vec(c, a2, a3, b[2], b[3]);
        if (j < 8) {
            if ((lane >> 2) == j) {
                r0 = c[0];
                r1 = c[1];
            }
        } else {
            r2 = c[0];
            r3 = c[1];
        }
    }
    ull* dst = g_attn1 + (size_t)e * D_MODEL + 72 * w + 2 * lane;
    ll_store2(dst, r0, r1, tag);
    if (lane < 4) ll_store2(dst + 64, r2, r3, tag);
    cons_sync();
}

__device__ __noinline__ void late_duty(unsigned char* smem, uint32_t tag) {
    const int tid = threadIdx.x, w = tid >> 5, lane = tid & 31;
    const int li = blockIdx.x - LATE0, g = li / 12, k12 = li % 12;
    const uint32_t sbase = smem_u32(smem);
    float* red2 = (float*)(smem + OFF_RED2);
    float* st = (float*)(smem + OFF_ST);
    float* est = red2 + 512;
    uint32_t b[4][4];
    TC(24);
    mbar_wait(sbase + BAR_WL, 0);
    if (w < 6) {
#pragma unroll
        for (int k = 0; k < 4; k++) ldsm_x4t(sbase + OFF_WL + (lane + 32 * k) * 96 + w * 16, b[k]);
    }
    {
        const ull* rec = g_opart + (size_t)(g * HPG + 7) * GSZ * RECW;
        float ov[13][2];
        const bool has_st = tid >= 64 && tid < 64 + GSZ;
        const ull* base = rec + (tid >> 6) * RECW + 2 * (tid & 63);
        const ull* last = tid < 64 ? base + 32 * RECW : rec + (tid - 64) * RECW + 128;
        const ull* ex = g_attn1 + (size_t)(g * 28 + (tid / 24) * 4) * D_MODEL + 48 * k12 + 2 * (tid % 24);
        ll_pollf<13>([&](int i) { return i > 8 ? ex + (i - 9) * D_MODEL : (i == 8 ? last : base + i * 4 * RECW); },
                     ((tid < 64 || has_st) ? 0x1ffu : 0xffu) | (tid < 168 ? 0x1e00u : 0u), ov, tag);
        TC(25);
        if (has_st) *(float2*)(st + 2 * (tid - 64)) = make_float2(ov[8][0], ov[8][1]);
        if (tid < 168)
            *(float2*)(est + 2 * tid) = make_float2((ov[9][0] + ov[10][0]) + (ov[11][0] + ov[12][0]),
                                                    (ov[9][1] + ov[10][1]) + (ov[11][1] + ov[12][1]));
        cons_sync();
        if (tid == 0) ll_store2(g_pre + 2 * li, 0.f, 0.f, tag);
        if (GU_GATE == 2 && tid == 0) mbar_arrive(sbase + BAR_GU);
        float wb;
        const float wa = record_weights(st, lane, wb);
        TC(26);
        float s0 = 0.f, s1 = 0.f;
#pragma unroll
        for (int i = 0; i < 8; i++) {
            const float wt = __shfl_sync(0xffffffffu, wa, (tid >> 6) + 4 * i);
            s0 = fmaf(wt, ov[i][0], s0);
            s1 = fmaf(wt, ov[i][1], s1);
        }
        if (tid < 64) {
            s0 = fmaf(wb, ov[8][0], s0);
            s1 = fmaf(wb, ov[8][1], s1);
        }
        *(float2*)(red2 + (tid >> 6) * 128 + 2 * (tid & 63)) = make_float2(s0, s1);
    }
    cons_sync();
    TL(4);
    if (w < 6) {
        uint32_t pk[2];
#pragma unroll
        for (int hf = 0; hf < 2; hf++) {
            const float* r = red2 + 64 * hf + 2 * lane;
            const float2 t0 = *(const float2*)r, t1 = *(const float2*)(r + 128), t2 = *(const float2*)(r + 256),
                         t3 = *(const float2*)(r + 384);
            pk[hf] = pack_bf16((t0.x + t1.x) + (t2.x + t3.x), (t0.y + t1.y) + (t2.y + t3.y));
        }
        float c0[4] = {0.f, 0.f, 0.f, 0.f}, c1[4] = {0.f, 0.f, 0.f, 0.f};
#pragma unroll
        for (int k = 0; k < 4; k++) {
            const uint32_t src = pk[k >> 1];
            const int l0 = 16 * (k & 1) + (lane & 3);
            mma_vec(c0, __shfl_sync(0xffffffffu, src, l0), __shfl_sync(0xffffffffu, src, l0 + 4), b[k][0], b[k][1]);
            mma_vec(c1, __shfl_sync(0xffffffffu, src, l0 + 8), __shfl_sync(0xffffffffu, src, l0 + 12), b[k][2], b[k][3]);
        }
        const int col = 8 * w + 2 * (lane & 3);
        float r0 = c0[0] + c1[0], r1 = c0[1] + c1[1];
#pragma unroll
        for (int h = 0; h < 7; h++) {
            const float2 t = *(const float2*)(est + h * 48 + col);
            r0 += t.x;
            r1 += t.y;
        }
        if (lane < 4 * NREP)
            ll_store2(g_attn2 + (size_t)((lane >> 2) * NGRP + g) * D_MODEL + 48 * k12 + col, r0, r1, tag);
    }
    TC(27);
    cons_sync();
}

__device__ __noinline__ void mlp_tail(unsigned char* smem, int slot, uint32_t ph, uint32_t parked, uint32_t tag,
                                      bf16* __restrict__ out) {
    const int n_parked = __popc(parked);
    const int tid = threadIdx.x, w = tid >> 5, lane = tid & 31;
    const int cta = blockIdx.x;
    const uint32_t sbase = smem_u32(smem);
    const uint32_t bar_full = sbase + OFF_BAR;
    float* xs = (float*)(smem + OFF_XS);
    float* hs = (float*)(smem + OFF_HS);
    float* red2 = (float*)(smem + OFF_RED2);
    const uint32_t vn_a = sbase + OFF_VN + (lane & 3) * 4;
    auto tail_wait = [&](int t) -> uint32_t {
        int s;
        uint32_t p;
        if (t < n_parked) {
            const uint32_t e = ((volatile uint32_t*)(smem + OFF_CLM))[t];
            s = e & 255u;
            p = e >> 8;
        } else {
            s = slot;
            p = ph;
            for (int k = n_parked; k < t; k++) {
                do {
                    if (++s == NSLOT) {
                        s = 0;
                        p ^= 1;
                    }
                } while (parked >> s & 1u);
            }
        }
        mbar_wait(bar_full + 8 * s, p);
        return sbase + s * TBYTES;
    };
    const int m = w >> 2, kq = w & 3;
    uint32_t bA[9][4], bB[9][4], bC[9][2];
    {
        const uint32_t lrow = ((lane >> 3) & 1) * 8 + (lane & 7);
        const uint32_t lcol = (lane >> 4) * 16;
#pragma unroll
        for (int p = 0; p < 3; p++) {
            const uint32_t tb = tail_wait(2 * p + m);
#pragma unroll
            for (int s = 0; s < 3; s++) {
                const uint32_t ra = tb + ((3 * kq + s) * 16 + lrow) * 80;
                ldsm_x4t(ra + lcol, bA[3 * p + s]);
                ldsm_x4t(ra + 32 + lcol, bB[3 * p + s]);
                ldsm_x2t(ra + 64, bC[3 * p + s][0], bC[3 * p + s][1]);
            }
        }
    }
    TC(0);
    {
        if (w == 0) {
            float sv[2][2];
            ll_poll<2>(g_pre + 2 * lane, 64, lane < 16 ? 2 : 1, sv, tag);
        }
        cons_sync();
        TL(7);
        TC(1);
        float v[8][2];
        const ull* ab = g_attn2 + (size_t)(cta % NREP) * NGRP * D_MODEL + 2 * tid;
        ll_pollf<8>([&](int i) { return ab + (i & 3) * D_MODEL + (i >> 2) * 512; }, tid < 32 ? 0xffu : 0xfu, v, tag);
        TC(2);
        const float2 xa = *(const float2*)(xs + 2 * tid);
        const float2 xb = *(const float2*)(xs + 512 + 2 * (tid & 31));
        float hv[4];
        hv[0] = bf16r(xa.x + bf16r((v[0][0] + v[1][0]) + (v[2][0] + v[3][0])));
        hv[1] = bf16r(xa.y + bf16r((v[0][1] + v[1][1]) + (v[2][1] + v[3][1])));
        hv[2] = bf16r(xb.x + bf16r((v[4][0] + v[5][0]) + (v[6][0] + v[7][0])));
        hv[3] = bf16r(xb.y + bf16r((v[4][1] + v[5][1]) + (v[6][1] + v[7][1])));
        *(float2*)(hs + 2 * tid) = make_float2(hv[0], hv[1]);
        if (tid < 32) *(float2*)(hs + 512 + 2 * tid) = make_float2(hv[2], hv[3]);
        TC(3);
        ln_block(smem, hv, tid);
    }
    cons_sync();
    TL(8);
    TC(4);
    {
        float c[2][5][4];
#pragma unroll
        for (int j = 0; j < 10; j++) c[j / 5][j % 5][0] = c[j / 5][j % 5][1] = c[j / 5][j % 5][2] = c[j / 5][j % 5][3] = 0.f;
#pragma unroll
        for (int i = 0; i < 9; i++) {
            const uint32_t ka = vn_a + (192 * (i / 3) + (3 * kq + i % 3) * 16) * 2;
            const uint32_t al = lds32(ka), ah = lds32(ka + 16);
            mma_vec(c[i & 1][0], al, ah, bA[i][0], bA[i][1]);
            mma_vec(c[i & 1][1], al, ah, bA[i][2], bA[i][3]);
            mma_vec(c[i & 1][2], al, ah, bB[i][0], bB[i][1]);
            mma_vec(c[i & 1][3], al, ah, bB[i][2], bB[i][3]);
            mma_vec(c[i & 1][4], al, ah, bC[i][0], bC[i][1]);
        }
        if (lane < 4) {
#pragma unroll
            for (int j = 0; j < 5; j++)
                *(float2*)(red2 + w * 40 + 8 * j + 2 * lane) = make_float2(c[0][j][0] + c[1][j][0], c[0][j][1] + c[1][j][1]);
        }
    }
    uint32_t b[9][4], bt[9];
    {
        mbar_wait(sbase + BAR_DN, 0);
        const uint32_t boxb = sbase + OFF_DN + w * 144;
        const uint32_t box = boxb + lane * RPITCH;
        const uint32_t boxt = boxb + (32 + (lane & 3)) * RPITCH;
#pragma unroll
        for (int j = 0; j < 9; j++) {
            ldsm_x4t(box + j * 16, b[j]);
            ldsm_x1t(boxt + j * 16, bt[j]);
        }
    }
    cons_sync();
    TC(5);
    {
        uint32_t pk = 0u;
        {
            const float* rc = red2 + 2 * min(lane, 17) + ((36 * cta) & 7);
            float r[2];
#pragma unroll
            for (int j = 0; j < 2; j++) {
                const float g = bf16r((rc[j] + rc[40 + j]) + (rc[80 + j] + rc[120 + j]));
                const float u = bf16r((rc[160 + j] + rc[200 + j]) + (rc[240 + j] + rc[280 + j]));
                const float inner = 0.7978845608028654f * (g + 0.044715f * g * g * g);
                r[j] = bf16r(__fdividef(g, 1.0f + __expf(-2.0f * inner))) * u;
            }
            if (lane < 18) pk = pack_bf16(r[0], r[1]);
        }
        const uint32_t a0 = __shfl_sync(0xffffffffu, pk, lane & 3), a1 = __shfl_sync(0xffffffffu, pk, 4 + (lane & 3));
        const uint32_t a2 = __shfl_sync(0xffffffffu, pk, 8 + (lane & 3)), a3 = __shfl_sync(0xffffffffu, pk, 12 + (lane & 3));
        const uint32_t a4 = __shfl_sync(0xffffffffu, pk, 16 + (lane & 3));
        TL(9);
        TC(6);
        float r0 = 0.f, r1 = 0.f, r2 = 0.f, r3 = 0.f;
#pragma unroll
        for (int j = 0; j < 9; j++) {
            float c[4] = {0.f, 0.f, 0.f, 0.f};
            mma_vec(c, a0, a1, b[j][0], b[j][1]);
            mma_vec(c, a2, a3, b[j][2], b[j][3]);
            mma_vec(c, a4, 0u, bt[j], 0u);
            if (j < 8) {
                if ((lane >> 2) == j) {
                    r0 = c[0];
                    r1 = c[1];
                }
            } else {
                r2 = c[0];
                r3 = c[1];
            }
        }
        ull* dst = g_down + (size_t)((9 * w + (lane >> 2)) * NOWN + cta) * 8 + 2 * (lane & 3);
        ll_store2(dst, r0, r1, tag);
        if (lane < 4) ll_store2(dst + (size_t)8 * NOWN * 8, r2, r3, tag);
    }
    TC(7);
    TL(10);
    if (cta < NRED) {
        float v[2][2];
        ll_poll<2>(g_down + (size_t)cta * NOWN * 8 + 2 * tid, 512, 2, v, tag);
        TC(8);
        float r0 = v[0][0] + v[1][0], r1 = v[0][1] + v[1][1];
#pragma unroll
        for (int o = 4; o <= 16; o <<= 1) {
            r0 += __shfl_xor_sync(0xffffffffu, r0, o);
            r1 += __shfl_xor_sync(0xffffffffu, r1, o);
        }
        if (lane < 4) *(float2*)(red2 + 512 + w * 8 + 2 * lane) = make_float2(r0, r1);
        cons_sync();
        if (tid < 8) {
            float r = 0.f;
#pragma unroll
            for (int i = 0; i < 8; i++) r += red2[512 + i * 8 + tid];
            const bf16 o = __float2bfloat16_rn(hs[8 * cta + tid] + bf16r(r));
            out[8 * cta + tid] = o;
        }
        if (cta == 0 && tid == 0) {
            *(uint4*)g_ctr = make_uint4(0u, 0u, 0u, 0u);
            g_epoch = tag;
        }
    }
    TL(11);
    TC(9);
}

__global__ void __launch_bounds__(NTHREADS, 1)
fused_decode_kernel(const __grid_constant__ CUtensorMap tm_wq, const __grid_constant__ CUtensorMap tm_wo,
                    const __grid_constant__ CUtensorMap tm_g, const __grid_constant__ CUtensorMap tm_u,
                    const bf16* __restrict__ wo, const bf16* __restrict__ wg, const bf16* __restrict__ wu,
                    const bf16* __restrict__ wd, const bf16* __restrict__ x,
                    const bf16* __restrict__ kc, const bf16* __restrict__ vc, bf16* __restrict__ out) {
    extern __shared__ __align__(1024) unsigned char smem[];
    const int tid = threadIdx.x;
    const int cta = blockIdx.x;
    const int grp = cta % NGRP;
    const int cig = cta / NGRP;
    const bool owner = cta < NOWN;
    const bool early = cta < NEARLY, late = cta >= LATE0 && cta < NOWN;

    const uint32_t sbase = smem_u32(smem);
    const uint32_t bar_full = sbase + OFF_BAR;
    const uint32_t bar_empty = bar_full + NSLOT * 8;
    volatile uint32_t* desc = (volatile uint32_t*)(smem + OFF_DESC);

    if (tid >= 256) {
        if (tid == 256) {
#pragma unroll
            for (int i = 0; i < NSLOT; i++) {
                mbar_init(bar_full + 8 * i, 1);
                mbar_init(bar_empty + 8 * i, 8);
            }
#pragma unroll
            for (int i = 0; i < 6; i++) mbar_init(sbase + BAR_DN + 8 * i, 1);

            asm volatile("fence.mbarrier_init.release.cluster;" ::: "memory");
            asm volatile("fence.proxy.async.shared::cta;" ::: "memory");
        }
        __syncwarp();
        asm volatile("bar.arrive 2, 288;" ::: "memory");
        if (tid != 256) return;

        uint64_t pol;
        asm volatile("createpolicy.fractional.L2::evict_first.b64 %0, 1.0;" : "=l"(pol));
        const char* kbase = (const char*)kc + (size_t)grp * UPG * TBYTES;
        const char* vbase = (const char*)vc + (size_t)grp * UPG * TBYTES;
        int wq_pend = 0;
        if (owner) {
#pragma unroll 1
            for (int p = 0; p < 3; p++) {
                mbar_expect_tx(sbase + BAR_WQ + 8 * p, 15360);
                tma2d(sbase + OFF_DN + p * 15360, &tm_wq, 32 * cta, 192 * p, sbase + BAR_WQ + 8 * p, pol);
            }
            wq_pend = 3;
        }
        uint32_t na = (uint32_t)(cig - LOOK * GSZ), nb = (uint32_t)(GSZ + cig - LOOK * GSZ);
        uint32_t wo_at = early ? (uint32_t)((cta >> 2) % 7 + 1) * 256u + 128u : END_MARK;
        int slot = 0, lslot = 0;
        uint32_t ph = 0, lph = 0;
        int infl = 0;
        int cap = INFL;
        uint32_t lskip = 0, lnext = 0;
        bool swept = false;
        uint32_t n_units = 0;
        int gu = 0;
        uint32_t parked = 0;
        const int park_n = owner ? (late ? PARK_L : PARK_N) : 0;
        auto load_down = [&]() {
            mbar_expect_tx(sbase + BAR_DN, 36 * 1152);
#pragma unroll 1
            for (int r = 0; r < 36; r++)
                bulk_load(sbase + OFF_DN + r * RPITCH, (const char*)wd + (size_t)(36 * cta + r) * 1152, 1152, sbase + BAR_DN, pol);
        };
        int kind = 0;
        uint32_t u = 0;
#pragma unroll 1
        while (true) {
            if (kind == 0) {
                if (LOOK == 1 || (n_units & 1) == 0) u = na + LOOK * GSZ;
                else u = nb + LOOK * GSZ;
                if (u >= UPG) {
                    swept = true;
                    cap = INFL_TAIL;
                    kind = wo_at != END_MARK ? 2 : 5;
                    wo_at = END_MARK;
                } else if (u >= wo_at) {
                    kind = 2;
                    wo_at = END_MARK;
                } else if (gu < park_n && u >= UPG - PARK_AT) {
                    kind = 6;
                } else {
                    if (LOOK == 1 || (n_units & 1) == 0) {
                        asm volatile("atom.relaxed.gpu.global.add.u32 %0, [%1], 1;" : "=r"(na) : "l"(&g_ctr[grp]) : "memory");
                    } else {
                        asm volatile("atom.relaxed.gpu.global.add.u32 %0, [%1], 1;" : "=r"(nb) : "l"(&g_ctr[grp]) : "memory");
                    }
                    if (++n_units == 7 && owner) {
                        if (!DN_LATE) load_down();
                        if (late) {
                            mbar_expect_tx(sbase + BAR_WL, 12288);
                            tma2d(sbase + OFF_WL, &tm_wo, 48 * ((cta - LATE0) % 12), 128 * (((cta - LATE0) / 12) * HPG + 7),
                                  sbase + BAR_WL, pol);
                        }
                    }
                }
            }
            if (wq_pend) {
                mbar_wait(sbase + BAR_WQ + 8 * (3 - wq_pend), 0);
                wq_pend--;
            }
            while (infl >= cap) {
                mbar_wait(bar_full + 8 * lslot, lph);
                lskip |= lnext;
                do {
                    if (++lslot == NSLOT) {
                        lslot = 0;
                        lph ^= 1;
                    }
                } while (lskip >> lslot & 1u);
                lnext = parked & (1u << lslot);
                infl--;
            }
            mbar_wait(bar_empty + 8 * slot, ph ^ 1);
            infl++;
            const uint32_t dst = sbase + slot * TBYTES;
            const uint32_t fb = bar_full + 8 * slot;
            if (kind < 2) {
                desc[slot] = u;
                mbar_expect_tx(fb, TBYTES);
                bulk_load(dst, (kind ? vbase : kbase) + (size_t)u * TBYTES, TBYTES, fb, pol);
                kind ^= 1;
            } else if (kind < 5) {
                const int oh = (cta / 28) * HPG + (cta >> 2) % 7;
                const char* src = (const char*)wo + (size_t)(128 * oh + 32 * (cta & 3) + 11 * (kind - 2)) * 1152;
                const int nr = kind == 4 ? 10 : 11;
                desc[slot] = WO_MARK;
                mbar_expect_tx(fb, nr * 1152);
#pragma unroll 1
                for (int r = 0; r < nr; r++) bulk_load(dst + r * RPITCH, src + (size_t)r * 1152, 1152, fb, pol);
                kind = kind == 4 ? 0 : kind + 1;
            } else if (kind == 5) {
                desc[slot] = END_MARK;
                mbar_arrive(fb);
                if (!owner) break;
                if (GU_GATE) mbar_wait(sbase + BAR_GU, 0);
                kind = 6;
            } else {
                desc[slot] = GU_MARK;
                ((volatile uint32_t*)(smem + OFF_CLM))[gu] = (uint32_t)slot | ph << 8;
                mbar_expect_tx(fb, 15360);
                tma2d(dst, (gu & 1) ? &tm_u : &tm_g, (36 * cta) & ~7, 192 * (gu >> 1), fb, pol);
                parked |= 1u << slot;
                if (slot == lslot) lnext = 1u << slot;
                if (++gu == DN_LATE) load_down();
                if (gu == 6) break;
                if (!swept && gu == park_n) kind = 0;
            }
            do {
                if (++slot == NSLOT) {
                    slot = 0;
                    ph ^= 1;
                }
            } while (parked >> slot & 1u);
        }
        return;
    }

    const int w = tid >> 5, lane = tid & 31;
    float* red = (float*)(smem + OFF_RED);
    float* qs = (float*)(smem + OFF_Q);

    TL(0);
    const uint32_t tag = *(volatile unsigned int*)&g_epoch + 1u;
    q_phase(smem, x, owner, tag);

    int slot = 0;
    uint32_t ph = 0;
    uint32_t parked = 0;
    auto advance = [&]() {
        do {
            if (++slot == NSLOT) {
                slot = 0;
                ph ^= 1;
            }
        } while (parked >> slot & 1u);
    };
    auto release = [&]() {
        __syncwarp();
        if (lane == 0) mbar_arrive(bar_empty + 8 * slot);
        advance();
    };

    TL(2);

    const int hw = lane >> 4, ch = lane & 15;
    const uint32_t tile_off = (8 * w + hw) * 256 + ch * 16;
    const bool b3 = (lane & 8) != 0, b2 = (lane & 4) != 0;
    int cur = 0;
    float m_run = -INFINITY, l_run = 0.f;
    float acc[8], qf[8];
#pragma unroll
    for (int j = 0; j < 8; j++) {
        acc[j] = 0.f;
        qf[j] = qs[ch * 8 + j];
    }
    uint32_t n_units = 0;

    auto flush_upto = [&](int upto) {
#pragma unroll 1
        for (; cur < upto; cur++) {
            if (cur == CLR_HEAD) {
                const uint4 z = make_uint4(0u, 0u, 0u, 0u);
                if (cta < NRED) {
                    uint4* d = (uint4*)(g_down + (size_t)cta * NOWN * 8);
                    d[tid] = z;
                    d[tid + 256] = z;
                }
                if (cta < NREP * NGRP * 2 && tid < 144) ((uint4*)g_attn2)[cta * 144 + tid] = z;
                if (cta == NCTA - 1 && tid < NLATE) ((uint4*)g_pre)[tid] = z;
                if (tid < RECW / 2) ((uint4*)(g_opart + (size_t)((grp * HPG + 7) * GSZ + cig) * RECW))[tid] = z;
                __threadfence();
            }
            float* rb = red + (cur & 1) * (8 * RECW);
#pragma unroll
            for (int j = 0; j < 8; j++) acc[j] += __shfl_xor_sync(0xffffffffu, acc[j], 16);
            const float lw = l_run + __shfl_xor_sync(0xffffffffu, l_run, 16);
            if (lane < 16) {
                *(float4*)(rb + w * RECW + ch * 8) = make_float4(acc[0], acc[1], acc[2], acc[3]);
                *(float4*)(rb + w * RECW + ch * 8 + 4) = make_float4(acc[4], acc[5], acc[6], acc[7]);
                if (lane == 0) *(float2*)(rb + w * RECW + 128) = make_float2(m_run, lw);
            }
            cons_sync();
            if (tid < 129) {
                float M = -INFINITY;
#pragma unroll
                for (int i = 0; i < 8; i++) M = fmaxf(M, rb[i * RECW + 128]);
                const int col = tid < 128 ? tid : 129;
                float s = 0.f;
#pragma unroll
                for (int i = 0; i < 8; i++) {
                    const float mi = rb[i * RECW + 128];
                    const float sc = mi == -INFINITY ? 0.f : __expf(mi - M);
                    s = fmaf(sc, rb[i * RECW + col], s);
                }
                ull* rec = g_opart + (size_t)((grp * HPG + cur) * GSZ + cig) * RECW;
                if (tid < 128) ll_store1(rec + tid, s, tag);
                else {
                    ll_store2(rec + 128, M, s, tag);
                    ll_store2(rec + 130, 0.f, 0.f, tag);
                }
            }
            m_run = -INFINITY;
            l_run = 0.f;
#pragma unroll
            for (int j = 0; j < 8; j++) acc[j] = 0.f;
            if (cur + 1 < HPG) {
#pragma unroll
                for (int j = 0; j < 8; j++) qf[j] = qs[(cur + 1) * 128 + ch * 8 + j];
            }
        }
    };

#pragma unroll 1
    while (true) {
        mbar_wait(bar_full + 8 * slot, ph);
        const uint32_t u = desc[slot];
        if (u < (uint32_t)UPG) {
            if ((int)(u >> 8) != cur) flush_upto(u >> 8);
            const unsigned char* tp = smem + slot * TBYTES + tile_off;
            float d[4];
#pragma unroll
            for (int i = 0; i < 4; i++) {
                const uint4 v = *(const uint4*)(tp + i * 512);
                float a = bf_lo(v.x) * qf[0];
                float b = bf_hi(v.x) * qf[1];
                a = fmaf(bf_lo(v.y), qf[2], a);
                b = fmaf(bf_hi(v.y), qf[3], b);
                a = fmaf(bf_lo(v.z), qf[4], a);
                b = fmaf(bf_hi(v.z), qf[5], b);
                a = fmaf(bf_lo(v.w), qf[6], a);
                b = fmaf(bf_hi(v.w), qf[7], b);
                d[i] = a + b;
            }
            release();
            float k0 = b3 ? d[2] : d[0];
            float k1 = b3 ? d[3] : d[1];
            k0 += __shfl_xor_sync(0xffffffffu, b3 ? d[0] : d[2], 8);
            k1 += __shfl_xor_sync(0xffffffffu, b3 ? d[1] : d[3], 8);
            float kk = b2 ? k1 : k0;
            kk += __shfl_xor_sync(0xffffffffu, b2 ? k0 : k1, 4);
            kk += __shfl_xor_sync(0xffffffffu, kk, 2);
            kk += __shfl_xor_sync(0xffffffffu, kk, 1);
            kk = bf16r(bf16r(kk) * 0.08838834764831845f);
            float p[4];
#pragma unroll
            for (int i = 0; i < 4; i++) p[i] = __shfl_sync(0xffffffffu, kk, (lane & 16) + 4 * i);
            float mx = fmaxf(fmaxf(p[0], p[1]), fmaxf(p[2], p[3]));
            mx = fmaxf(mx, __shfl_xor_sync(0xffffffffu, mx, 16));
            if (mx > m_run) {
                const float sc = __expf(m_run - mx);
                m_run = mx;
                l_run *= sc;
#pragma unroll
                for (int j = 0; j < 8; j++) acc[j] *= sc;
            }
#pragma unroll
            for (int i = 0; i < 4; i++) {
                p[i] = __expf(p[i] - m_run);
                l_run += p[i];
            }
            mbar_wait(bar_full + 8 * slot, ph);
            tp = smem + slot * TBYTES + tile_off;
#pragma unroll
            for (int i = 0; i < 4; i++) {
                const uint4 v = *(const uint4*)(tp + i * 512);
                acc[0] = fmaf(p[i], bf_lo(v.x), acc[0]);
                acc[1] = fmaf(p[i], bf_hi(v.x), acc[1]);
                acc[2] = fmaf(p[i], bf_lo(v.y), acc[2]);
                acc[3] = fmaf(p[i], bf_hi(v.y), acc[3]);
                acc[4] = fmaf(p[i], bf_lo(v.z), acc[4]);
                acc[5] = fmaf(p[i], bf_hi(v.z), acc[5]);
                acc[6] = fmaf(p[i], bf_lo(v.w), acc[6]);
                acc[7] = fmaf(p[i], bf_hi(v.w), acc[7]);
            }
            release();
            n_units++;
        } else if (u == GU_MARK) {
            parked |= 1u << slot;
            advance();
        } else if (u == WO_MARK) {
            early_duty(smem, slot, ph, parked, tag);
            release();
            release();
            release();
        } else {
            release();
            break;
        }
    }
    flush_upto(HPG);
    TL(6);
    if (GU_GATE == 1 || (GU_GATE == 2 && !late)) {
        cons_sync();
        if (tid == 0) mbar_arrive(sbase + BAR_GU);
    }
    if (late) {
        late_duty(smem, tag);
        TL(5);
    }
    if (!owner) return;

    mlp_tail(smem, slot, ph, parked, tag, out);
}

typedef CUresult (*EncodeFn)(CUtensorMap*, CUtensorMapDataType, cuuint32_t, void*, const cuuint64_t*, const cuuint64_t*,
                             const cuuint32_t*, const cuuint32_t*, CUtensorMapInterleave, CUtensorMapSwizzle,
                             CUtensorMapL2promotion, CUtensorMapFloatOOBfill);

void make_map(EncodeFn fn, CUtensorMap* m, const void* ptr, uint64_t rows, uint64_t cols, uint32_t box_rows,
              uint32_t box_cols) {
    cuuint64_t dims[2] = {cols, rows};
    cuuint64_t strides[1] = {cols * 2};
    cuuint32_t box[2] = {box_cols, box_rows};
    cuuint32_t es[2] = {1, 1};
    fn(m, CU_TENSOR_MAP_DATA_TYPE_BFLOAT16, 2, const_cast<void*>(ptr), dims, strides, box, es,
       CU_TENSOR_MAP_INTERLEAVE_NONE, CU_TENSOR_MAP_SWIZZLE_NONE, CU_TENSOR_MAP_L2_PROMOTION_NONE,
       CU_TENSOR_MAP_FLOAT_OOB_FILL_NONE);
}

}

extern "C" void kernel_launch(void* const* d_in, const int* in_sizes, int n_in, void* d_out, int out_size) {
    (void)in_sizes;
    (void)n_in;
    (void)out_size;
    static EncodeFn encode = nullptr;
    if (!encode) {
        void* fn = nullptr;
        cudaDriverEntryPointQueryResult st;
        cudaGetDriverEntryPoint("cuTensorMapEncodeTiled", &fn, cudaEnableDefault, &st);
        encode = (EncodeFn)fn;
        cudaFuncSetAttribute(fused_decode_kernel, cudaFuncAttributeMaxDynamicSharedMemorySize, SMEM_BYTES);
    }
    const bf16* x = (const bf16*)d_in[0];
    const bf16* kc = (const bf16*)d_in[1];
    const bf16* vc = (const bf16*)d_in[2];
    CUtensorMap tm_wq, tm_wo, tm_g, tm_u;
    make_map(encode, &tm_wq, d_in[3], 576, 4096, 192, 40);
    make_map(encode, &tm_wo, d_in[4], 4096, 576, 128, 48);
    make_map(encode, &tm_g, d_in[6], 576, 4608, 192, 40);
    make_map(encode, &tm_u, d_in[7], 576, 4608, 192, 40);
    fused_decode_kernel<<<NCTA, NTHREADS, SMEM_BYTES, cudaStreamPerThread>>>(tm_wq, tm_wo, tm_g, tm_u, (const bf16*)d_in[4],
                                                                             (const bf16*)d_in[6], (const bf16*)d_in[7],
                                                                             (const bf16*)d_in[8], x, kc, vc,
                                                                             (bf16*)d_out);
}
```

```cpp
#include <cuda_runtime.h>
#include <cuda_bf16.h>
#include <cuda.h>
#include <stdint.h>

#define DEVINL __device__ __forceinline__
typedef unsigned long long ull;
typedef __nv_bfloat16 bf16;

namespace {

constexpr int D_MODEL = 576;
constexpr int NCTA = 132;
constexpr int NOWN = 128;
constexpr int NGRP = 4;
constexpr int GSZ = 33;
constexpr int HPG = 8;
constexpr int TBYTES = 16384;
constexpr int UPG = 2048;
constexpr int NSLOT = 9;
constexpr int INFL = 3;
constexpr int INFL_TAIL = 2;
constexpr int CLR_HEAD = 5;
constexpr int NREP = 4;
constexpr int NTHREADS = 288;
constexpr int NEARLY = 112;
constexpr int NLATE = 48;
__host__ __device__ constexpr int late_index(int cta) {
    return cta < 112 ? (cta % 28 < 8 ? (cta / 28) * 8 + cta % 28 : -1) : (cta < 128 ? cta - 80 : -1);
}
constexpr int NRED = 72;
constexpr int RECW = 132;
constexpr uint32_t END_MARK = 0xFFFFFFFFu;
constexpr uint32_t WO_MARK = 0xFFFFFFFEu;
constexpr long long WAIT_LIMIT = 200000000LL;

constexpr int RPITCH = 1168;
constexpr int OFF_DN = NSLOT * TBYTES;
constexpr int OFF_WL = OFF_DN + 42112;
constexpr int OFF_Q = OFF_WL + 12288;
constexpr int OFF_RED = OFF_Q + 4096;
constexpr int OFF_RED2 = OFF_RED + 8448;
constexpr int OFF_XS = OFF_RED2 + 4096;
constexpr int OFF_HS = OFF_XS + 2304;
constexpr int OFF_VN = OFF_HS + 2304;
constexpr int OFF_ST = OFF_VN + 1152;
constexpr int OFF_DESC = OFF_ST + 272;
constexpr int OFF_LNP = OFF_DESC + 48;
constexpr int OFF_BAR = OFF_LNP + 64;
constexpr int BAR_DN = OFF_BAR + 2 * NSLOT * 8;
constexpr int BAR_WQ = BAR_DN + 8;
constexpr int BAR_WL = BAR_WQ + 3 * 8;
constexpr int SMEM_BYTES = BAR_WL + 8;
static_assert(SMEM_BYTES <= 232448, "smem");
static_assert(OFF_LNP % 16 == 0 && OFF_BAR % 8 == 0 && OFF_ST % 8 == 0, "align");

__device__ unsigned int g_epoch;
__device__ __align__(16) unsigned int g_ctr[NGRP];
__device__ __align__(128) ull g_q[4 * 4096];
__device__ __align__(128) ull g_opart[32 * GSZ * RECW];
__device__ __align__(128) ull g_attn1[NEARLY * D_MODEL];
__device__ __align__(128) ull g_attn2[NREP * NGRP * D_MODEL];
__device__ __align__(128) ull g_pre[NLATE * 2];
__device__ __align__(128) ull g_down[NRED * NOWN * 8];

DEVINL uint32_t smem_u32(const void* p) { return (uint32_t)__cvta_generic_to_shared(p); }
DEVINL void mbar_init(uint32_t bar, uint32_t cnt) {
    asm volatile("mbarrier.init.shared::cta.b64 [%0], %1;" ::"r"(bar), "r"(cnt) : "memory");
}
DEVINL void mbar_expect_tx(uint32_t bar, uint32_t bytes) {
    asm volatile("mbarrier.arrive.expect_tx.shared::cta.b64 _, [%0], %1;" ::"r"(bar), "r"(bytes) : "memory");
}
DEVINL void mbar_arrive(uint32_t bar) {
    asm volatile("mbarrier.arrive.shared::cta.b64 _, [%0];" ::"r"(bar) : "memory");
}
__device__ __noinline__ long long wait_check(long long t0) {
    const long long t = clock64();
    if (t0 == 0) return t;
    if (t - t0 > WAIT_LIMIT) __trap();
    return t0;
}
DEVINL void mbar_wait(uint32_t bar, uint32_t parity) {
    uint32_t ok;
    uint32_t it = 0;
    long long t0 = 0;
    while (true) {
        asm volatile(
            "{\n.reg .pred p;\nmbarrier.try_wait.parity.shared::cta.b64 p, [%1], %2;\nselp.u32 %0, 1, 0, p;\n}"
            : "=r"(ok)
            : "r"(bar), "r"(parity)
            : "memory");
        if (ok) break;
        if ((++it & 63u) == 0) t0 = wait_check(t0);
    }
}
DEVINL void bulk_load(uint32_t dst, const void* src, uint32_t bytes, uint32_t bar, uint64_t pol) {
    asm volatile(
        "cp.async.bulk.shared::cluster.global.mbarrier::complete_tx::bytes.L2::cache_hint [%0], [%1], %2, [%3], %4;" ::"r"(dst),
        "l"(src), "r"(bytes), "r"(bar), "l"(pol)
        : "memory");
}
DEVINL void tma2d(uint32_t dst, const CUtensorMap* map, int c0, int c1, uint32_t bar, uint64_t pol) {
    asm volatile(
        "cp.async.bulk.tensor.2d.shared::cluster.global.mbarrier::complete_tx::bytes.L2::cache_hint [%0], [%1, {%3, %4}], [%2], %5;" ::"r"(dst),
        "l"((uint64_t)map), "r"(bar), "r"(c0), "r"(c1), "l"(pol)
        : "memory");
}
DEVINL void cons_sync() { asm volatile("bar.sync 1, 256;" ::: "memory"); }

DEVINL void ldsm_x4t(uint32_t addr, uint32_t (&r)[4]) {
    asm volatile("ldmatrix.sync.aligned.m8n8.x4.trans.shared.b16 {%0,%1,%2,%3}, [%4];"
                 : "=r"(r[0]), "=r"(r[1]), "=r"(r[2]), "=r"(r[3])
                 : "r"(addr)
                 : "memory");
}
DEVINL void ldsm_x4(uint32_t addr, uint32_t (&r)[4]) {
    asm volatile("ldmatrix.sync.aligned.m8n8.x4.shared.b16 {%0,%1,%2,%3}, [%4];"
                 : "=r"(r[0]), "=r"(r[1]), "=r"(r[2]), "=r"(r[3])
                 : "r"(addr)
                 : "memory");
}
DEVINL void ldsm_x2t(uint32_t addr, uint32_t& r0, uint32_t& r1) {
    asm volatile("ldmatrix.sync.aligned.m8n8.x2.trans.shared.b16 {%0,%1}, [%2];" : "=r"(r0), "=r"(r1) : "r"(addr) : "memory");
}
DEVINL void ldsm_x1t(uint32_t addr, uint32_t& r0) {
    asm volatile("ldmatrix.sync.aligned.m8n8.x1.trans.shared.b16 {%0}, [%1];" : "=r"(r0) : "r"(addr) : "memory");
}
DEVINL uint32_t lds32(uint32_t addr) {
    uint32_t r;
    asm volatile("ld.shared.u32 %0, [%1];" : "=r"(r) : "r"(addr) : "memory");
    return r;
}
DEVINL void mma_vec(float (&c)[4], uint32_t a_lo, uint32_t a_hi, uint32_t b0, uint32_t b1) {
    asm("mma.sync.aligned.m16n8k16.row.col.f32.bf16.bf16.f32 {%0,%1,%2,%3}, {%4,%5,%6,%7}, {%8,%9}, {%0,%1,%2,%3};"
        : "+f"(c[0]), "+f"(c[1]), "+f"(c[2]), "+f"(c[3])
        : "r"(a_lo), "r"(0u), "r"(a_hi), "r"(0u), "r"(b0), "r"(b1));
}

DEVINL uint32_t pack_bf16(float lo, float hi) {
    uint32_t r;
    asm("cvt.rn.bf16x2.f32 %0, %1, %2;" : "=r"(r) : "f"(hi), "f"(lo));
    return r;
}
DEVINL float bf16r(float v) { return __uint_as_float(pack_bf16(0.f, v) & 0xffff0000u); }
DEVINL float bf_lo(uint32_t w) { return __uint_as_float(w << 16); }
DEVINL float bf_hi(uint32_t w) { return __uint_as_float(w & 0xffff0000u); }

DEVINL ull ll_pack(float v, uint32_t tag) { return ((ull)tag << 32) | (ull)__float_as_uint(v); }
DEVINL void ll_store1(ull* p, float a, uint32_t tag) {
    asm volatile("st.relaxed.gpu.global.u64 [%0], %1;" ::"l"(p), "l"(ll_pack(a, tag)) : "memory");
}
DEVINL void ll_store2(ull* p, float a, float b, uint32_t tag) {
    asm volatile("st.relaxed.gpu.global.v2.u64 [%0], {%1, %2};" ::"l"(p), "l"(ll_pack(a, tag)), "l"(ll_pack(b, tag)) : "memory");
}
DEVINL void ll_load2(const ull* p, ull& a, ull& b) {
    asm volatile("ld.relaxed.gpu.global.v2.u64 {%0, %1}, [%2];" : "=l"(a), "=l"(b) : "l"(p) : "memory");
}
DEVINL bool ll_ok(ull a, ull b, uint32_t tag) { return (uint32_t)(a >> 32) == tag && (uint32_t)(b >> 32) == tag; }
DEVINL float ll_val(ull a) { return __uint_as_float((uint32_t)a); }

template <int N, class F>
DEVINL void ll_pollf(F addr, uint32_t pend, float (&v)[N][2], uint32_t tag) {
#pragma unroll
    for (int i = 0; i < N; i++) v[i][0] = v[i][1] = 0.f;
    uint32_t it = 0;
    long long t0 = 0;
    while (pend) {
        ull a[N], b[N];
#pragma unroll
        for (int i = 0; i < N; i++)
            if (pend >> i & 1u) ll_load2(addr(i), a[i], b[i]);
#pragma unroll
        for (int i = 0; i < N; i++)
            if ((pend >> i & 1u) && ll_ok(a[i], b[i], tag)) {
                v[i][0] = ll_val(a[i]);
                v[i][1] = ll_val(b[i]);
                pend &= ~(1u << i);
            }
        if ((++it & 63u) == 0) t0 = wait_check(t0);
    }
}
template <int N>
DEVINL void ll_poll(const ull* base, int stride, int cnt, float (&v)[N][2], uint32_t tag) {
    ll_pollf<N>([&](int i) { return base + i * stride; }, (1u << cnt) - 1u, v, tag);
}

DEVINL float warp_sum(float v) {
#pragma unroll
    for (int o = 16; o > 0; o >>= 1) v += __shfl_xor_sync(0xffffffffu, v, o);
    return v;
}
DEVINL float warp_max(float v) {
#pragma unroll
    for (int o = 16; o > 0; o >>= 1) v = fmaxf(v, __shfl_xor_sync(0xffffffffu, v, o));
    return v;
}

DEVINL void ln_block(unsigned char* smem, const float (&v)[4], int tid) {
    float* part = (float*)(smem + OFF_LNP);
    float mu = 0.5f * (v[0] + v[1]), m2 = 0.5f * (v[0] - v[1]) * (v[0] - v[1]), hn = 1.0f;
    if (tid < 32) {
        const float mu2 = 0.5f * (v[2] + v[3]), d = mu - mu2;
        m2 += fmaf(d, d, 0.5f * (v[2] - v[3]) * (v[2] - v[3]));
        mu = 0.5f * (mu + mu2);
        hn = 2.0f;
    }
#pragma unroll
    for (int o = 16; o > 0; o >>= 1) {
        const float mo = __shfl_xor_sync(0xffffffffu, mu, o), so = __shfl_xor_sync(0xffffffffu, m2, o);
        const float d = mu - mo;
        m2 = fmaf(d * d, hn, m2 + so);
        mu = 0.5f * (mu + mo);
        hn *= 2.0f;
    }
    if ((tid & 31) == 0) *(float2*)(part + 2 * (tid >> 5)) = make_float2(mu, m2);
    cons_sync();
    const float4 q0 = *(const float4*)part, q1 = *(const float4*)(part + 4), q2 = *(const float4*)(part + 8),
                 q3 = *(const float4*)(part + 12);
    const float mean = (((q0.x + q0.x) + q0.z) + (q1.x + q1.z) + ((q2.x + q2.z) + (q3.x + q3.z))) * (1.0f / 9.0f);
    const float d0 = q0.x - mean, d1 = q0.z - mean, d2 = q1.x - mean, d3 = q1.z - mean, d4 = q2.x - mean,
                d5 = q2.z - mean, d6 = q3.x - mean, d7 = q3.z - mean;
    const float dd = ((2.0f * d0 * d0 + d1 * d1) + (d2 * d2 + d3 * d3)) + ((d4 * d4 + d5 * d5) + (d6 * d6 + d7 * d7));
    const float M2 = fmaf(64.0f, dd, ((q0.y + q0.w) + (q1.y + q1.w)) + ((q2.y + q2.w) + (q3.y + q3.w)));
    const float mb = bf16r(mean);
    const float vb = bf16r(M2 * (1.0f / 576.0f));
    const float den = bf16r(sqrtf(bf16r(vb + 1e-5f)));
    uint32_t* vn2 = (uint32_t*)(smem + OFF_VN);
    const uint32_t n0 = pack_bf16(bf16r(v[0] - mb) / den, bf16r(v[1] - mb) / den);
    vn2[tid] = n0;
    if (tid < 32) {
        const uint32_t n1 = pack_bf16(bf16r(v[2] - mb) / den, bf16r(v[3] - mb) / den);
        vn2[256 + tid] = n1;
    }
}

__device__ __noinline__ uint32_t q_phase(unsigned char* smem, const bf16* __restrict__ x, bool owner) {
    const int tid = threadIdx.x, w = tid >> 5, lane = tid & 31;
    const int cta = blockIdx.x, grp = cta % NGRP;
    const uint32_t sbase = smem_u32(smem);
    float* xs = (float*)(smem + OFF_XS);
    float* qs = (float*)(smem + OFF_Q);
    const uint32_t* x2 = (const uint32_t*)x;
    const uint32_t xa = __ldg(x2 + tid), xb = tid < 32 ? __ldg(x2 + 256 + tid) : 0u;
    const uint32_t tag = *(volatile unsigned int*)&g_epoch + 1u;
    if (owner) {
        const float xv4[4] = {bf_lo(xa), bf_hi(xa), bf_lo(xb), bf_hi(xb)};
        *(float2*)(xs + 2 * tid) = make_float2(xv4[0], xv4[1]);
        if (tid < 32) *(float2*)(xs + 512 + 2 * tid) = make_float2(xv4[2], xv4[3]);
        ln_block(smem, xv4, tid);
    }
    asm volatile("bar.sync 2, 288;" ::: "memory");
    if (owner) {
        float c0[4] = {0.f, 0.f, 0.f, 0.f}, c1[4] = {0.f, 0.f, 0.f, 0.f};
        const uint32_t lrow = ((lane >> 3) & 1) * 8 + (lane & 7);
        const uint32_t lcol = (2 * w + (lane >> 4)) * 16;
        const uint32_t vn_a = sbase + OFF_VN + 288 * (cta & 3) + (lane & 3) * 4;
#pragma unroll
        for (int p = 0; p < 3; p++) {
            mbar_wait(sbase + BAR_WQ + 8 * p, 0);
#pragma unroll
            for (int s = 0; s < 3; s++) {
                uint32_t b[4];
                ldsm_x4t(sbase + OFF_DN + ((3 * p + s) * 16 + lrow) * 272 + lcol, b);
                const uint32_t al = lds32(vn_a + (3 * p + s) * 32), ah = lds32(vn_a + (3 * p + s) * 32 + 16);
                mma_vec(c0, al, ah, b[0], b[1]);
                mma_vec(c1, al, ah, b[2], b[3]);
            }
        }
        if (lane < 8) {
            const int h = cta >> 2;
            ull* dst = g_q + (size_t)((h >> 3) * 4 + (cta & 3)) * 1024 + (h & 7) * 128 + 16 * w + 2 * lane;
            ll_store2(dst, lane < 4 ? c0[0] : c1[0], lane < 4 ? c0[1] : c1[1], tag);
        }
    }
    if (tid < 64) {
        float v[4][2];
        ll_poll<4>(g_q + (size_t)grp * 4096 + 2 * tid, 1024, 4, v, tag);
        *(float2*)(qs + 2 * tid) = make_float2(bf16r((v[0][0] + v[1][0]) + (v[2][0] + v[3][0])),
                                               bf16r((v[0][1] + v[1][1]) + (v[2][1] + v[3][1])));
    }
    cons_sync();
    return tag;
}

__device__ __noinline__ void q_rest(unsigned char* smem, uint32_t tag) {
    const int tid = threadIdx.x, grp = blockIdx.x % NGRP;
    float* qs = (float*)(smem + OFF_Q);
    float v[8][2];
    const ull* qb = g_q + (size_t)grp * 4096 + 2 * tid;
    ll_pollf<8>([&](int i) { return qb + (i & 3) * 1024 + (i >> 2) * 512; }, tid < 64 ? 0xf0u : 0xffu, v, tag);
    if (tid >= 64)
        *(float2*)(qs + 2 * tid) = make_float2(bf16r((v[0][0] + v[1][0]) + (v[2][0] + v[3][0])),
                                               bf16r((v[0][1] + v[1][1]) + (v[2][1] + v[3][1])));
    *(float2*)(qs + 2 * tid + 512) = make_float2(bf16r((v[4][0] + v[5][0]) + (v[6][0] + v[7][0])),
                                                 bf16r((v[4][1] + v[5][1]) + (v[6][1] + v[7][1])));
}

DEVINL float record_weights(const float* st, int lane, float& wb) {
    const float2 sa = *(const float2*)(st + 2 * lane), sb = *(const float2*)(st + 64);
    const float M = fmaxf(warp_max(sa.x), sb.x);
    const float ea = sa.x == -INFINITY ? 0.f : __expf(sa.x - M);
    const float eb = sb.x == -INFINITY ? 0.f : __expf(sb.x - M);
    const float inv = 1.0f / fmaf(eb, sb.y, warp_sum(ea * sa.y));
    wb = eb * inv;
    return ea * inv;
}

__device__ __noinline__ void early_duty(unsigned char* smem, int slot, uint32_t ph, uint32_t tag) {
    const int tid = threadIdx.x, w = tid >> 5, lane = tid & 31;
    const int e = blockIdx.x, oh = (e / 28) * HPG + (e >> 2) % 7, oj = e & 3;
    const uint32_t sbase = smem_u32(smem);
    float* red2 = (float*)(smem + OFF_RED2);
    float* st = (float*)(smem + OFF_ST);
    const ull* rec = g_opart + (size_t)oh * GSZ * RECW;
    {
        float ov[3][2];
        const bool has_st = tid >= 64 && tid < 64 + GSZ;
        const ull* base = rec + (tid >> 4) * RECW + 32 * oj + 2 * (tid & 15);
        const ull* last = tid < 16 ? base + 32 * RECW : rec + (tid - 64) * RECW + 128;
        ll_pollf<3>([&](int i) { return i == 2 ? last : base + i * 16 * RECW; }, (tid < 16 || has_st) ? 7u : 3u, ov, tag);
        if (has_st) *(float2*)(st + 2 * (tid - 64)) = make_float2(ov[2][0], ov[2][1]);
        cons_sync();
        float wb;
        const float wa = record_weights(st, lane, wb);
        const float w0 = __shfl_sync(0xffffffffu, wa, tid >> 4), w1 = __shfl_sync(0xffffffffu, wa, (tid >> 4) + 16);
        float s0 = fmaf(w0, ov[0][0], w1 * ov[1][0]), s1 = fmaf(w0, ov[0][1], w1 * ov[1][1]);
        if (tid < 16) {
            s0 = fmaf(wb, ov[2][0], s0);
            s1 = fmaf(wb, ov[2][1], s1);
        }
        s0 += __shfl_xor_sync(0xffffffffu, s0, 16);
        s1 += __shfl_xor_sync(0xffffffffu, s1, 16);
        if (lane < 16) *(float2*)(red2 + w * 32 + 2 * lane) = make_float2(s0, s1);
    }
    cons_sync();
    uint32_t pk;
    {
        float s0 = 0.f, s1 = 0.f;
#pragma unroll
        for (int i = 0; i < 8; i++) {
            const float2 t = *(const float2*)(red2 + i * 32 + 2 * (lane & 15));
            s0 += t.x;
            s1 += t.y;
        }
        pk = pack_bf16(s0, s1);
    }
    const uint32_t a0 = __shfl_sync(0xffffffffu, pk, lane & 3), a1 = __shfl_sync(0xffffffffu, pk, 4 + (lane & 3));
    const uint32_t a2 = __shfl_sync(0xffffffffu, pk, 8 + (lane & 3)), a3 = __shfl_sync(0xffffffffu, pk, 12 + (lane & 3));
    uint32_t row;
    {
        int s = slot;
        uint32_t p2 = ph;
        row = 0;
#pragma unroll
        for (int t = 0; t < 3; t++) {
            mbar_wait(sbase + OFF_BAR + 8 * s, p2);
            if (lane / 11 == t) row = sbase + s * TBYTES + (lane % 11) * RPITCH + w * 144;
            if (++s == NSLOT) {
                s = 0;
                p2 ^= 1;
            }
        }
    }
    float r0 = 0.f, r1 = 0.f, r2 = 0.f, r3 = 0.f;
#pragma unroll
    for (int j = 0; j < 9; j++) {
        uint32_t b[4];
        ldsm_x4t(row + j * 16, b);
        float c[4] = {0.f, 0.f, 0.f, 0.f};
        mma_vec(c, a0, a1, b[0], b[1]);
        mma_vec(c, a2, a3, b[2], b[3]);
        if (j < 8) {
            if ((lane >> 2) == j) {
                r0 = c[0];
                r1 = c[1];
            }
        } else {
            r2 = c[0];
            r3 = c[1];
        }
    }
    ull* dst = g_attn1 + (size_t)e * D_MODEL + 72 * w + 2 * lane;
    ll_store2(dst, r0, r1, tag);
    if (lane < 4) ll_store2(dst + 64, r2, r3, tag);
    cons_sync();
}

__device__ __noinline__ void late_duty(unsigned char* smem, uint32_t tag) {
    const int tid = threadIdx.x, w = tid >> 5, lane = tid & 31;
    const int li = late_index(blockIdx.x), g = li / 12, k12 = li % 12;
    const uint32_t sbase = smem_u32(smem);
    float* red2 = (float*)(smem + OFF_RED2);
    float* est = red2 + 512;
    uint32_t b[4][4];
    float inv;
    mbar_wait(sbase + BAR_WL, 0);
    if (w < 6) {
#pragma unroll
        for (int k = 0; k < 4; k++) ldsm_x4t(sbase + OFF_WL + (lane + 32 * k) * 96 + w * 16, b[k]);
    }
    {
        const ull* rec = g_opart + (size_t)(g * HPG + 7) * GSZ * RECW;
        float* st = (float*)(smem + OFF_ST);
        float ov[13][2];
        const bool has_st = tid >= 64 && tid < 64 + GSZ;
        const ull* base = rec + (tid >> 6) * RECW + 2 * (tid & 63);
        const ull* last = tid < 64 ? base + 32 * RECW : rec + (tid - 64) * RECW + 128;
        const ull* ex = g_attn1 + (size_t)(g * 28 + (tid / 24) * 4) * D_MODEL + 48 * k12 + 2 * (tid % 24);
        ll_pollf<13>([&](int i) { return i > 8 ? ex + (i - 9) * D_MODEL : (i == 8 ? last : base + i * 4 * RECW); },
                     ((tid < 64 || has_st) ? 0x1ffu : 0xffu) | (tid < 168 ? 0x1e00u : 0u), ov, tag);
        if (has_st) *(float2*)(st + 2 * (tid - 64)) = make_float2(ov[8][0], ov[8][1]);
        if (tid < 168)
            *(float2*)(est + 2 * tid) = make_float2((ov[9][0] + ov[10][0]) + (ov[11][0] + ov[12][0]),
                                                    (ov[9][1] + ov[10][1]) + (ov[11][1] + ov[12][1]));
        cons_sync();
        if (tid == 0) ll_store2(g_pre + 2 * li, 0.f, 0.f, tag);
        const float2 sa = *(const float2*)(st + 2 * lane), sb = *(const float2*)(st + 64);
        const float M = fmaxf(warp_max(sa.x), sb.x);
        const float ea = sa.x == -INFINITY ? 0.f : __expf(sa.x - M);
        const float eb = sb.x == -INFINITY ? 0.f : __expf(sb.x - M);
        inv = 1.0f / fmaf(eb, sb.y, warp_sum(ea * sa.y));
        float s0 = 0.f, s1 = 0.f;
        if (tid < 64) {
            s0 = eb * ov[8][0];
            s1 = eb * ov[8][1];
        }
#pragma unroll
        for (int i = 0; i < 8; i++) {
            const float wt = __shfl_sync(0xffffffffu, ea, (tid >> 6) + 4 * i);
            s0 = fmaf(wt, ov[i][0], s0);
            s1 = fmaf(wt, ov[i][1], s1);
        }
        *(float2*)(red2 + (tid >> 6) * 128 + 2 * (tid & 63)) = make_float2(s0, s1);
    }
    cons_sync();
    if (w < 6) {
        uint32_t pk[2];
#pragma unroll
        for (int hf = 0; hf < 2; hf++) {
            const float* r = red2 + 64 * hf + 2 * lane;
            const float2 t0 = *(const float2*)r, t1 = *(const float2*)(r + 128), t2 = *(const float2*)(r + 256),
                         t3 = *(const float2*)(r + 384);
            pk[hf] = pack_bf16(((t0.x + t1.x) + (t2.x + t3.x)) * inv, ((t0.y + t1.y) + (t2.y + t3.y)) * inv);
        }
        float c0[4] = {0.f, 0.f, 0.f, 0.f}, c1[4] = {0.f, 0.f, 0.f, 0.f};
#pragma unroll
        for (int k = 0; k < 4; k++) {
            const uint32_t src = pk[k >> 1];
            const int l0 = 16 * (k & 1) + (lane & 3);
            mma_vec(c0, __shfl_sync(0xffffffffu, src, l0), __shfl_sync(0xffffffffu, src, l0 + 4), b[k][0], b[k][1]);
            mma_vec(c1, __shfl_sync(0xffffffffu, src, l0 + 8), __shfl_sync(0xffffffffu, src, l0 + 12), b[k][2], b[k][3]);
        }
        const int col = 8 * w + 2 * (lane & 3);
        float r0 = c0[0] + c1[0], r1 = c0[1] + c1[1];
#pragma unroll
        for (int h = 0; h < 7; h++) {
            const float2 t = *(const float2*)(est + h * 48 + col);
            r0 += t.x;
            r1 += t.y;
        }
        if (lane < 4 * NREP)
            ll_store2(g_attn2 + (size_t)((lane >> 2) * NGRP + g) * D_MODEL + 48 * k12 + col, r0, r1, tag);
    }
    cons_sync();
}

__device__ __noinline__ void mlp_tail(unsigned char* smem, int slot, uint32_t ph, uint32_t tag, bf16* __restrict__ out) {
    const int tid = threadIdx.x, w = tid >> 5, lane = tid & 31;
    const int cta = blockIdx.x;
    const uint32_t sbase = smem_u32(smem);
    const uint32_t bar_full = sbase + OFF_BAR;
    float* xs = (float*)(smem + OFF_XS);
    float* hs = (float*)(smem + OFF_HS);
    float* red2 = (float*)(smem + OFF_RED2);
    auto tail_wait = [&](int t) -> uint32_t {
        int s = slot + t;
        uint32_t p = ph;
        if (s >= NSLOT) {
            s -= NSLOT;
            p ^= 1;
        }
        mbar_wait(bar_full + 8 * s, p);
        return sbase + s * TBYTES;
    };
    const int m = w >> 2, kq = w & 3;
    uint32_t bA[9][4], bB[9][4], bC[9][2];
    {
        const uint32_t lrow = ((lane >> 3) & 1) * 8 + (lane & 7);
        const uint32_t lcol = (lane >> 4) * 16;
#pragma unroll
        for (int p = 0; p < 3; p++) {
            const uint32_t tb = tail_wait(2 * p + m);
#pragma unroll
            for (int s = 0; s < 3; s++) {
                const uint32_t ra = tb + ((3 * kq + s) * 16 + lrow) * 80;
                ldsm_x4t(ra + lcol, bA[3 * p + s]);
                ldsm_x4t(ra + 32 + lcol, bB[3 * p + s]);
                ldsm_x2t(ra + 64, bC[3 * p + s][0], bC[3 * p + s][1]);
            }
        }
    }
    {
        if (w == 0) {
            float sv[2][2];
            ll_poll<2>(g_pre + 2 * lane, 64, lane < 16 ? 2 : 1, sv, tag);
        }
        cons_sync();
        float v[8][2];
        const ull* ab = g_attn2 + (size_t)(cta % NREP) * NGRP * D_MODEL + 2 * tid;
        ll_pollf<8>([&](int i) { return ab + (i & 3) * D_MODEL + (i >> 2) * 512; }, tid < 32 ? 0xffu : 0xfu, v, tag);
        const float2 xa = *(const float2*)(xs + 2 * tid);
        const float2 xb = *(const float2*)(xs + 512 + 2 * (tid & 31));
        float hv[4];
        hv[0] = bf16r(xa.x + bf16r((v[0][0] + v[1][0]) + (v[2][0] + v[3][0])));
        hv[1] = bf16r(xa.y + bf16r((v[0][1] + v[1][1]) + (v[2][1] + v[3][1])));
        hv[2] = bf16r(xb.x + bf16r((v[4][0] + v[5][0]) + (v[6][0] + v[7][0])));
        hv[3] = bf16r(xb.y + bf16r((v[4][1] + v[5][1]) + (v[6][1] + v[7][1])));
        *(float2*)(hs + 2 * tid) = make_float2(hv[0], hv[1]);
        if (tid < 32) *(float2*)(hs + 512 + 2 * tid) = make_float2(hv[2], hv[3]);
        ln_block(smem, hv, tid);
    }
    cons_sync();
    {
        float c[2][5][4];
#pragma unroll
        for (int j = 0; j < 10; j++) c[j / 5][j % 5][0] = c[j / 5][j % 5][1] = c[j / 5][j % 5][2] = c[j / 5][j % 5][3] = 0.f;
        uint32_t aa[3][4], ab[3][4];
#pragma unroll
        for (int p = 0; p < 3; p++) {
            const uint32_t ka = sbase + OFF_VN + (192 * p + 48 * kq) * 2 + (lane >> 3) * 16;
            ldsm_x4(ka, aa[p]);
            ldsm_x4(ka + 32, ab[p]);
        }
#pragma unroll
        for (int i = 0; i < 9; i++) {
            const uint32_t al = i % 3 == 0 ? aa[i / 3][0] : (i % 3 == 1 ? aa[i / 3][2] : ab[i / 3][2]);
            const uint32_t ah = i % 3 == 0 ? aa[i / 3][1] : (i % 3 == 1 ? aa[i / 3][3] : ab[i / 3][3]);
            mma_vec(c[i & 1][0], al, ah, bA[i][0], bA[i][1]);
            mma_vec(c[i & 1][1], al, ah, bA[i][2], bA[i][3]);
            mma_vec(c[i & 1][2], al, ah, bB[i][0], bB[i][1]);
            mma_vec(c[i & 1][3], al, ah, bB[i][2], bB[i][3]);
            mma_vec(c[i & 1][4], al, ah, bC[i][0], bC[i][1]);
        }
        if (lane < 4) {
#pragma unroll
            for (int j = 0; j < 5; j++)
                *(float2*)(red2 + w * 40 + 8 * j + 2 * lane) = make_float2(c[0][j][0] + c[1][j][0], c[0][j][1] + c[1][j][1]);
        }
    }
    uint32_t b[9][4], bt[9];
    {
        mbar_wait(sbase + BAR_DN, 0);
        const uint32_t boxb = sbase + OFF_DN + w * 144;
        const uint32_t box = boxb + lane * RPITCH;
        const uint32_t boxt = boxb + (32 + (lane & 3)) * RPITCH;
#pragma unroll
        for (int j = 0; j < 9; j++) {
            ldsm_x4t(box + j * 16, b[j]);
            ldsm_x1t(boxt + j * 16, bt[j]);
        }
    }
    cons_sync();
    {
        uint32_t pk = 0u;
        {
            const float* rc = red2 + 2 * min(lane, 17) + ((36 * cta) & 7);
            float r[2];
#pragma unroll
            for (int j = 0; j < 2; j++) {
                const float g = bf16r((rc[j] + rc[40 + j]) + (rc[80 + j] + rc[120 + j]));
                const float u = bf16r((rc[160 + j] + rc[200 + j]) + (rc[240 + j] + rc[280 + j]));
                const float inner = 0.7978845608028654f * (g + 0.044715f * g * g * g);
                r[j] = bf16r(__fdividef(g, 1.0f + __expf(-2.0f * inner))) * u;
            }
            if (lane < 18) pk = pack_bf16(r[0], r[1]);
        }
        const uint32_t a0 = __shfl_sync(0xffffffffu, pk, lane & 3), a1 = __shfl_sync(0xffffffffu, pk, 4 + (lane & 3));
        const uint32_t a2 = __shfl_sync(0xffffffffu, pk, 8 + (lane & 3)), a3 = __shfl_sync(0xffffffffu, pk, 12 + (lane & 3));
        const uint32_t a4 = __shfl_sync(0xffffffffu, pk, 16 + (lane & 3));
        float r0 = 0.f, r1 = 0.f, r2 = 0.f, r3 = 0.f;
#pragma unroll
        for (int j = 0; j < 9; j++) {
            float c[4] = {0.f, 0.f, 0.f, 0.f};
            mma_vec(c, a0, a1, b[j][0], b[j][1]);
            mma_vec(c, a2, a3, b[j][2], b[j][3]);
            mma_vec(c, a4, 0u, bt[j], 0u);
            if (j < 8) {
                if ((lane >> 2) == j) {
                    r0 = c[0];
                    r1 = c[1];
                }
            } else {
                r2 = c[0];
                r3 = c[1];
            }
        }
        ull* dst = g_down + (size_t)((9 * w + (lane >> 2)) * NOWN + cta) * 8 + 2 * (lane & 3);
        ll_store2(dst, r0, r1, tag);
        if (lane < 4) ll_store2(dst + (size_t)8 * NOWN * 8, r2, r3, tag);
    }
    if (cta < NRED) {
        float v[2][2];
        ll_poll<2>(g_down + (size_t)cta * NOWN * 8 + 2 * tid, 512, 2, v, tag);
        float r0 = v[0][0] + v[1][0], r1 = v[0][1] + v[1][1];
#pragma unroll
        for (int o = 4; o <= 16; o <<= 1) {
            r0 += __shfl_xor_sync(0xffffffffu, r0, o);
            r1 += __shfl_xor_sync(0xffffffffu, r1, o);
        }
        if (lane < 4) *(float2*)(red2 + 512 + w * 8 + 2 * lane) = make_float2(r0, r1);
        cons_sync();
        if (tid < 8) {
            float r = 0.f;
#pragma unroll
            for (int i = 0; i < 8; i++) r += red2[512 + i * 8 + tid];
            const bf16 o = __float2bfloat16_rn(hs[8 * cta + tid] + bf16r(r));
            out[8 * cta + tid] = o;
        }
        if (cta == 0 && tid == 0) {
            *(uint4*)g_ctr = make_uint4(0u, 0u, 0u, 0u);
            g_epoch = tag;
        }
    }
}

__global__ void __launch_bounds__(NTHREADS, 1)
fused_decode_kernel(const __grid_constant__ CUtensorMap tm_wq, const __grid_constant__ CUtensorMap tm_wo,
                    const __grid_constant__ CUtensorMap tm_g, const __grid_constant__ CUtensorMap tm_u,
                    const bf16* __restrict__ wo, const bf16* __restrict__ wd, const bf16* __restrict__ x,
                    const bf16* __restrict__ kc, const bf16* __restrict__ vc, bf16* __restrict__ out) {
    extern __shared__ __align__(1024) unsigned char smem[];
    const int tid = threadIdx.x;
    const int cta = blockIdx.x;
    const int grp = cta % NGRP;
    const int cig = cta / NGRP;
    const bool owner = cta < NOWN;
    const bool early = cta < NEARLY, late = late_index(cta) >= 0;

    const uint32_t sbase = smem_u32(smem);
    const uint32_t bar_full = sbase + OFF_BAR;
    const uint32_t bar_empty = bar_full + NSLOT * 8;
    volatile uint32_t* desc = (volatile uint32_t*)(smem + OFF_DESC);

    if (tid >= 256) {
        if (tid == 256) {
#pragma unroll
            for (int i = 0; i < NSLOT; i++) {
                mbar_init(bar_full + 8 * i, 1);
                mbar_init(bar_empty + 8 * i, 8);
            }
#pragma unroll
            for (int i = 0; i < 5; i++) mbar_init(sbase + BAR_DN + 8 * i, 1);
            asm volatile("fence.mbarrier_init.release.cluster;" ::: "memory");
            asm volatile("fence.proxy.async.shared::cta;" ::: "memory");
        }
        __syncwarp();
        asm volatile("bar.arrive 2, 288;" ::: "memory");
        if (tid != 256) return;

        uint64_t pol;
        asm volatile("createpolicy.fractional.L2::evict_first.b64 %0, 1.0;" : "=l"(pol));
        const char* kbase = (const char*)kc + (size_t)grp * UPG * TBYTES;
        const char* vbase = (const char*)vc + (size_t)grp * UPG * TBYTES;
        int wq_pend = 0;
        if (owner) {
#pragma unroll 1
            for (int p = 0; p < 3; p++) {
                mbar_expect_tx(sbase + BAR_WQ + 8 * p, 48 * 272);
                tma2d(sbase + OFF_DN + p * 48 * 272, &tm_wq, 128 * (cta >> 2), 144 * (cta & 3) + 48 * p,
                      sbase + BAR_WQ + 8 * p, pol);
            }
            wq_pend = 3;
        }
        uint32_t nxt = (uint32_t)(cig - GSZ);
        uint32_t wo_at = early ? (uint32_t)((cta >> 2) % 7 + 1) * 256u + 128u : END_MARK;
        int slot = 0, lslot = 0;
        uint32_t ph = 0, lph = 0;
        int infl = 0;
        int cap = INFL;
        uint32_t n_units = 0;
        int kind = 0;
        uint32_t u = 0;
#pragma unroll 1
        while (true) {
            if (kind == 0) {
                u = nxt + GSZ;
                if (u >= UPG) {
                    cap = INFL_TAIL;
                    kind = wo_at != END_MARK ? 2 : 5;
                    wo_at = END_MARK;
                } else if (u >= wo_at) {
                    kind = 2;
                    wo_at = END_MARK;
                } else {
                    asm volatile("atom.relaxed.gpu.global.add.u32 %0, [%1], 1;" : "=r"(nxt) : "l"(&g_ctr[grp]) : "memory");
                    if (++n_units == 1 && late) {
                        mbar_expect_tx(sbase + BAR_WL, 12288);
                        tma2d(sbase + OFF_WL, &tm_wo, 48 * (late_index(cta) % 12), 128 * ((late_index(cta) / 12) * HPG + 7),
                              sbase + BAR_WL, pol);
                    }
                }
            }
            if (wq_pend) {
                mbar_wait(sbase + BAR_WQ + 8 * (3 - wq_pend), 0);
                wq_pend--;
            }
            while (infl >= cap) {
                mbar_wait(bar_full + 8 * lslot, lph);
                if (++lslot == NSLOT) {
                    lslot = 0;
                    lph ^= 1;
                }
                infl--;
            }
            mbar_wait(bar_empty + 8 * slot, ph ^ 1);
            infl++;
            const uint32_t dst = sbase + slot * TBYTES;
            const uint32_t fb = bar_full + 8 * slot;
            if (kind < 2) {
                desc[slot] = u;
                mbar_expect_tx(fb, TBYTES);
                bulk_load(dst, (kind ? vbase : kbase) + (size_t)u * TBYTES, TBYTES, fb, pol);
                kind ^= 1;
            } else if (kind < 5) {
                const int oh = (cta / 28) * HPG + (cta >> 2) % 7;
                const char* src = (const char*)wo + (size_t)(128 * oh + 32 * (cta & 3) + 11 * (kind - 2)) * 1152;
                const int nr = kind == 4 ? 10 : 11;
                desc[slot] = WO_MARK;
                mbar_expect_tx(fb, nr * 1152);
#pragma unroll 1
                for (int r = 0; r < nr; r++) bulk_load(dst + r * RPITCH, src + (size_t)r * 1152, 1152, fb, pol);
                kind = kind == 4 ? 0 : kind + 1;
            } else if (kind == 5) {
                desc[slot] = END_MARK;
                mbar_arrive(fb);
                if (!owner) break;
                kind = 6;
            } else {
                mbar_expect_tx(fb, 15360);
                tma2d(dst, (kind & 1) ? &tm_u : &tm_g, (36 * cta) & ~7, 192 * ((kind - 6) >> 1), fb, pol);
                if (++kind == 12) {
                    if (n_units < 4) mbar_wait(bar_empty, 0);
                    mbar_expect_tx(sbase + BAR_DN, 36 * 1152);
#pragma unroll 1
                    for (int r = 0; r < 36; r++)
                        bulk_load(sbase + OFF_DN + r * RPITCH, (const char*)wd + (size_t)(36 * cta + r) * 1152, 1152,
                                  sbase + BAR_DN, pol);
                    break;
                }
            }
            if (++slot == NSLOT) {
                slot = 0;
                ph ^= 1;
            }
        }
        return;
    }

    const int w = tid >> 5, lane = tid & 31;
    float* red = (float*)(smem + OFF_RED);
    float* qs = (float*)(smem + OFF_Q);

    const uint32_t tag = q_phase(smem, x, owner);

    int slot = 0;
    uint32_t ph = 0;
    auto release = [&]() {
        __syncwarp();
        if (lane == 0) mbar_arrive(bar_empty + 8 * slot);
        if (++slot == NSLOT) {
            slot = 0;
            ph ^= 1;
        }
    };

    const int hw = lane >> 4, ch = lane & 15;
    const uint32_t tile_off = (8 * w + hw) * 256 + ch * 16;
    const bool b3 = (lane & 8) != 0, b2 = (lane & 4) != 0;
    int cur = 0;
    float m_run = -INFINITY, l_run = 0.f;
    float acc[8], qf[8];
#pragma unroll
    for (int j = 0; j < 8; j++) {
        acc[j] = 0.f;
        qf[j] = qs[ch * 8 + j];
    }

    auto flush_upto = [&](int upto) {
#pragma unroll 1
        for (; cur < upto; cur++) {
            if (cur == 0) q_rest(smem, tag);
            if (cur == CLR_HEAD) {
                const uint4 z = make_uint4(0u, 0u, 0u, 0u);
                if (owner) {
                    ((uint4*)g_down)[((tid >> 2) * NOWN + cta) * 4 + (tid & 3)] = z;
                    if (tid < 32) ((uint4*)g_down)[((64 + (tid >> 2)) * NOWN + cta) * 4 + (tid & 3)] = z;
                }
                if (late) {
                    const int li = late_index(cta);
                    if (tid < 24 * NREP) ((uint4*)g_attn2)[((tid / 24) * NGRP + li / 12) * 288 + (li % 12) * 24 + tid % 24] = z;
                    if (tid == 255) ((uint4*)g_pre)[li] = z;
                }
                if (tid < RECW / 2) ((uint4*)(g_opart + (size_t)((grp * HPG + 7) * GSZ + cig) * RECW))[tid] = z;
                __threadfence();
            }
            float* rb = red + (cur & 1) * (8 * RECW);
#pragma unroll
            for (int j = 0; j < 8; j++) acc[j] += __shfl_xor_sync(0xffffffffu, acc[j], 16);
            const float lw = l_run + __shfl_xor_sync(0xffffffffu, l_run, 16);
            if (lane < 16) {
                *(float4*)(rb + w * RECW + ch * 8) = make_float4(acc[0], acc[1], acc[2], acc[3]);
                *(float4*)(rb + w * RECW + ch * 8 + 4) = make_float4(acc[4], acc[5], acc[6], acc[7]);
                if (lane == 0) *(float2*)(rb + w * RECW + 128) = make_float2(m_run, lw);
            }
            cons_sync();
            if (tid < 129) {
                float M = -INFINITY;
#pragma unroll
                for (int i = 0; i < 8; i++) M = fmaxf(M, rb[i * RECW + 128]);
                const int col = tid < 128 ? tid : 129;
                float s = 0.f;
#pragma unroll
                for (int i = 0; i < 8; i++) {
                    const float mi = rb[i * RECW + 128];
                    const float sc = mi == -INFINITY ? 0.f : __expf(mi - M);
                    s = fmaf(sc, rb[i * RECW + col], s);
                }
                ull* rec = g_opart + (size_t)((grp * HPG + cur) * GSZ + cig) * RECW;
                if (tid < 128) ll_store1(rec + tid, s, tag);
                else {
                    ll_store2(rec + 128, M, s, tag);
                    ll_store2(rec + 130, 0.f, 0.f, tag);
                }
            }
            m_run = -INFINITY;
            l_run = 0.f;
#pragma unroll
            for (int j = 0; j < 8; j++) acc[j] = 0.f;
            if (cur + 1 < HPG) {
#pragma unroll
                for (int j = 0; j < 8; j++) qf[j] = qs[(cur + 1) * 128 + ch * 8 + j];
            }
        }
    };

#pragma unroll 1
    while (true) {
        mbar_wait(bar_full + 8 * slot, ph);
        const uint32_t u = desc[slot];
        if (u < (uint32_t)UPG) {
            if ((int)(u >> 8) != cur) flush_upto(u >> 8);
            const unsigned char* tp = smem + slot * TBYTES + tile_off;
            float d[4];
#pragma unroll
            for (int i = 0; i < 4; i++) {
                const uint4 v = *(const uint4*)(tp + i * 512);
                float a = bf_lo(v.x) * qf[0];
                float b = bf_hi(v.x) * qf[1];
                a = fmaf(bf_lo(v.y), qf[2], a);
                b = fmaf(bf_hi(v.y), qf[3], b);
                a = fmaf(bf_lo(v.z), qf[4], a);
                b = fmaf(bf_hi(v.z), qf[5], b);
                a = fmaf(bf_lo(v.w), qf[6], a);
                b = fmaf(bf_hi(v.w), qf[7], b);
                d[i] = a + b;
            }
            release();
            float k0 = b3 ? d[2] : d[0];
            float k1 = b3 ? d[3] : d[1];
            k0 += __shfl_xor_sync(0xffffffffu, b3 ? d[0] : d[2], 8);
            k1 += __shfl_xor_sync(0xffffffffu, b3 ? d[1] : d[3], 8);
            float kk = b2 ? k1 : k0;
            kk += __shfl_xor_sync(0xffffffffu, b2 ? k0 : k1, 4);
            kk += __shfl_xor_sync(0xffffffffu, kk, 2);
            kk += __shfl_xor_sync(0xffffffffu, kk, 1);
            kk = bf16r(bf16r(kk) * 0.08838834764831845f);
            float p[4];
#pragma unroll
            for (int i = 0; i < 4; i++) p[i] = __shfl_sync(0xffffffffu, kk, (lane & 16) + 4 * i);
            float mx = fmaxf(fmaxf(p[0], p[1]), fmaxf(p[2], p[3]));
            mx = fmaxf(mx, __shfl_xor_sync(0xffffffffu, mx, 16));
            if (mx > m_run) {
                const float sc = __expf(m_run - mx);
                m_run = mx;
                l_run *= sc;
#pragma unroll
                for (int j = 0; j < 8; j++) acc[j] *= sc;
            }
#pragma unroll
            for (int i = 0; i < 4; i++) {
                p[i] = __expf(p[i] - m_run);
                l_run += p[i];
            }
            mbar_wait(bar_full + 8 * slot, ph);
            tp = smem + slot * TBYTES + tile_off;
#pragma unroll
            for (int i = 0; i < 4; i++) {
                const uint4 v = *(const uint4*)(tp + i * 512);
                acc[0] = fmaf(p[i], bf_lo(v.x), acc[0]);
                acc[1] = fmaf(p[i], bf_hi(v.x), acc[1]);
                acc[2] = fmaf(p[i], bf_lo(v.y), acc[2]);
                acc[3] = fmaf(p[i], bf_hi(v.y), acc[3]);
                acc[4] = fmaf(p[i], bf_lo(v.z), acc[4]);
                acc[5] = fmaf(p[i], bf_hi(v.z), acc[5]);
                acc[6] = fmaf(p[i], bf_lo(v.w), acc[6]);
                acc[7] = fmaf(p[i], bf_hi(v.w), acc[7]);
            }
            release();
        } else if (u == WO_MARK) {
            flush_upto((cta >> 2) % 7 + 1);
            early_duty(smem, slot, ph, tag);
            release();
            release();
            release();
        } else {
            release();
            break;
        }
    }
    flush_upto(HPG);
    if (late) late_duty(smem, tag);
    if (owner) mlp_tail(smem, slot, ph, tag, out);
}

__device__ float f_vec[2][D_MODEL], f_ln[D_MODEL], f_q[4096], f_o[4096], f_s[32 * 16384], f_hh[4608];

DEVINL float block_sum(float v, float* sh) {
    v = warp_sum(v);
    __syncthreads();
    if ((threadIdx.x & 31) == 0) sh[threadIdx.x >> 5] = v;
    __syncthreads();
    float r = 0.f;
    for (int i = 0; i < (int)(blockDim.x >> 5); i++) r += sh[i];
    return r;
}
__global__ void fb_ln(const bf16* x, const bf16* wo, int stage) {
    __shared__ float sh[32];
    const int t = threadIdx.x;
    float v = __bfloat162float(x[t]);
    if (stage) {
        float a = 0.f;
        for (int k = 0; k < 4096; k++) a = fmaf(f_o[k], __bfloat162float(wo[(size_t)k * D_MODEL + t]), a);
        v = bf16r(v + bf16r(a));
    }
    const float mean = block_sum(v, sh) / 576.0f;
    const float var = block_sum((v - mean) * (v - mean), sh) / 576.0f;
    f_vec[stage][t] = v;
    f_ln[t] = bf16r(bf16r(v - bf16r(mean)) / bf16r(sqrtf(bf16r(bf16r(var) + 1e-5f))));
}
__global__ void fb_q(const bf16* wq) {
    const int n = blockIdx.x * blockDim.x + threadIdx.x;
    float a = 0.f;
    for (int k = 0; k < D_MODEL; k++) a = fmaf(f_ln[k], __bfloat162float(wq[(size_t)k * 4096 + n]), a);
    f_q[n] = bf16r(a);
}
__global__ void fb_attn(const bf16* kc, const bf16* vc) {
    __shared__ float sh[32];
    const int h = blockIdx.x, t = threadIdx.x;
    float* sc = f_s + h * 16384;
    float m = -INFINITY;
    for (int i = t; i < 16384; i += 128) {
        float a = 0.f;
        for (int d = 0; d < 128; d++) a = fmaf(f_q[h * 128 + d], __bfloat162float(kc[((size_t)h * 16384 + i) * 128 + d]), a);
        sc[i] = bf16r(bf16r(a) * 0.08838834764831845f);
        m = fmaxf(m, sc[i]);
    }
    m = warp_max(m);
    if ((t & 31) == 0) sh[t >> 5] = m;
    __syncthreads();
    m = fmaxf(fmaxf(sh[0], sh[1]), fmaxf(sh[2], sh[3]));
    float l = 0.f;
    for (int i = t; i < 16384; i += 128) l += __expf(sc[i] - m);
    l = block_sum(l, sh);
    float a = 0.f;
    for (int i = 0; i < 16384; i++)
        a = fmaf(bf16r(__expf(sc[i] - m) / l), __bfloat162float(vc[((size_t)h * 16384 + i) * 128 + t]), a);
    f_o[h * 128 + t] = bf16r(a);
}
__global__ void fb_glu(const bf16* wg, const bf16* wu) {
    const int n = blockIdx.x * blockDim.x + threadIdx.x;
    float g = 0.f, u = 0.f;
    for (int k = 0; k < D_MODEL; k++) {
        g = fmaf(f_ln[k], __bfloat162float(wg[(size_t)k * 4608 + n]), g);
        u = fmaf(f_ln[k], __bfloat162float(wu[(size_t)k * 4608 + n]), u);
    }
    g = bf16r(g);
    f_hh[n] = bf16r(bf16r(0.5f * g * (1.0f + tanhf(0.7978845608028654f * (g + 0.044715f * g * g * g)))) * bf16r(u));
}
__global__ void fb_down(const bf16* wd, bf16* out) {
    const int n = blockIdx.x * blockDim.x + threadIdx.x;
    float a = 0.f;
    for (int k = 0; k < 4608; k++) a = fmaf(f_hh[k], __bfloat162float(wd[(size_t)k * D_MODEL + n]), a);
    out[n] = __float2bfloat16_rn(f_vec[1][n] + bf16r(a));
}

typedef CUresult (*EncodeFn)(CUtensorMap*, CUtensorMapDataType, cuuint32_t, void*, const cuuint64_t*, const cuuint64_t*,
                             const cuuint32_t*, const cuuint32_t*, CUtensorMapInterleave, CUtensorMapSwizzle,
                             CUtensorMapL2promotion, CUtensorMapFloatOOBfill);

void make_map(EncodeFn fn, CUtensorMap* m, const void* ptr, uint64_t rows, uint64_t cols, uint32_t box_rows,
              uint32_t box_cols) {
    cuuint64_t dims[2] = {cols, rows};
    cuuint64_t strides[1] = {cols * 2};
    cuuint32_t box[2] = {box_cols, box_rows};
    cuuint32_t es[2] = {1, 1};
    fn(m, CU_TENSOR_MAP_DATA_TYPE_BFLOAT16, 2, const_cast<void*>(ptr), dims, strides, box, es,
       CU_TENSOR_MAP_INTERLEAVE_NONE, CU_TENSOR_MAP_SWIZZLE_NONE, CU_TENSOR_MAP_L2_PROMOTION_L2_128B,
       CU_TENSOR_MAP_FLOAT_OOB_FILL_NONE);
}

}

extern "C" void kernel_launch(void* const* d_in, const int* in_sizes, int n_in, void* d_out, int out_size) {
    (void)in_sizes;
    (void)n_in;
    (void)out_size;
    static EncodeFn encode = nullptr;
    static int fused_ok = -1;
    if (fused_ok < 0) {
        void* fn = nullptr;
        cudaDriverEntryPointQueryResult st;
        cudaGetDriverEntryPoint("cuTensorMapEncodeTiled", &fn, cudaEnableDefault, &st);
        encode = (EncodeFn)fn;
        int dev = 0, sms = 0, per_sm = 0;
        cudaGetDevice(&dev);
        cudaDeviceGetAttribute(&sms, cudaDevAttrMultiProcessorCount, dev);
        const cudaError_t e =
            cudaFuncSetAttribute(fused_decode_kernel, cudaFuncAttributeMaxDynamicSharedMemorySize, SMEM_BYTES);
        if (e == cudaSuccess)
            cudaOccupancyMaxActiveBlocksPerMultiprocessor(&per_sm, fused_decode_kernel, NTHREADS, SMEM_BYTES);
        fused_ok = encode != nullptr && e == cudaSuccess && sms * per_sm >= NCTA;
        (void)cudaGetLastError();
    }
    const bf16* x = (const bf16*)d_in[0];
    const bf16* kc = (const bf16*)d_in[1];
    const bf16* vc = (const bf16*)d_in[2];
    if (!fused_ok) {
        cudaStream_t s = cudaStreamPerThread;
        fb_ln<<<1, D_MODEL, 0, s>>>(x, (const bf16*)d_in[4], 0);
        fb_q<<<32, 128, 0, s>>>((const bf16*)d_in[3]);
        fb_attn<<<32, 128, 0, s>>>(kc, vc);
        fb_ln<<<1, D_MODEL, 0, s>>>(x, (const bf16*)d_in[4], 1);
        fb_glu<<<36, 128, 0, s>>>((const bf16*)d_in[6], (const bf16*)d_in[7]);
        fb_down<<<9, 64, 0, s>>>((const bf16*)d_in[8], (bf16*)d_out);
        return;
    }
    CUtensorMap tm_wq, tm_wo, tm_g, tm_u;
    make_map(encode, &tm_wq, d_in[3], 576, 4096, 48, 136);
    make_map(encode, &tm_wo, d_in[4], 4096, 576, 128, 48);
    make_map(encode, &tm_g, d_in[6], 576, 4608, 192, 40);
    make_map(encode, &tm_u, d_in[7], 576, 4608, 192, 40);
    fused_decode_kernel<<<NCTA, NTHREADS, SMEM_BYTES, cudaStreamPerThread>>>(
        tm_wq, tm_wo, tm_g, tm_u, (const bf16*)d_in[4], (const bf16*)d_in[8], x, kc, vc, (bf16*)d_out);
}
```
